```python
import torch

def _softmax(x, axis=-1):
    return torch.softmax(x, dim=axis)

def _gelu(x):
    return torch.nn.functional.gelu(x, approximate='tanh')

def _silu(x):
    return torch.nn.functional.silu(x)

def _sigmoid(x):
    return torch.sigmoid(x)

def _layernorm(x, axis=-1, eps=1e-05):
    m = x.mean(dim=axis, keepdim=True)
    v = x.var(dim=axis, keepdim=True, unbiased=False)
    return (x - m) / torch.sqrt(v + eps)

def _scatter_add(tgt, idx, src, axis=0):
    return tgt.clone().index_add_(axis, idx, src)

def _segment_sum(src, seg, n):
    out = torch.zeros((n,) + src.shape[1:], dtype=src.dtype)
    return out.index_add_(0, seg, src)

def _pad(x, pw):
    flat = tuple((v for pair in reversed(pw) for v in pair))
    return torch.nn.functional.pad(x, flat)
kernel_name = 'concat_heads__sliding_block__memory_aug_recurrent_mem_tr__prompt'

def setup_inputs():

    _w = lambda a: (lambda t: t.to(torch.bfloat16) if t.is_floating_point() else t)(torch.as_tensor(a))

    def _A_setup():
        B, S, D = (1, 2048, 1024)
        return {'x': _w((lambda *s: torch.randn(*s, dtype=torch.bfloat16) * 0.2)(B, S, D)), 'wqkv': _w((lambda *s: torch.randn(*s, dtype=torch.bfloat16) * 0.2)(D, 3 * D)), 'wo': _w((lambda *s: torch.randn(*s, dtype=torch.bfloat16) * 0.05)(D, D))}
    _A_in = _A_setup()

    def _B_setup():
        B, S, Dm = (1, 2048, 1024)
        H, Dh = (32, 128)
        M, seg = (8, 32)
        seg = min(seg, S)
        S = S // seg * seg
        return {'x': _w((lambda *s: torch.randn(*s, dtype=torch.bfloat16) * 0.05)(B, S, Dm)), 'mem0': _w((lambda *s: torch.randn(*s, dtype=torch.bfloat16) * 1.6)(B, M, Dm)), 'Wq': _w((lambda *s: torch.randn(*s, dtype=torch.bfloat16) * 0.8)(Dm, H, Dh) * Dm ** (-0.5)), 'Wk': _w((lambda *s: torch.randn(*s, dtype=torch.bfloat16) * 0.8)(Dm, H, Dh) * Dm ** (-0.5)), 'Wv': _w((lambda *s: torch.randn(*s, dtype=torch.bfloat16) * 1.6)(Dm, H, Dh) * Dm ** (-0.5)), 'Wo': _w((lambda *s: torch.randn(*s, dtype=torch.bfloat16) * 1.6)(H, Dh, Dm) * (H * Dh) ** (-0.5)), 'seg_len': seg}
    _B_in = _B_setup()
    return {'A_x': _A_in['x'], 'A_wqkv': _A_in['wqkv'], 'A_wo': _A_in['wo'], 'B_x': _B_in['x'], 'B_mem0': _B_in['mem0'], 'B_Wq': _B_in['Wq'], 'B_Wk': _B_in['Wk'], 'B_Wv': _B_in['Wv'], 'B_Wo': _B_in['Wo'], 'B_seg_len': _B_in['seg_len']}

def reference(A_x, A_wqkv, A_wo, B_x, B_mem0, B_Wq, B_Wk, B_Wv, B_Wo, B_seg_len):

    def _A_ref(x, wqkv, wo):
        B, S, D = x.shape
        H = 32
        Dh = D // H
        W = 256
        qkv = (lambda x, *d: x.permute(*d))((x @ wqkv).reshape(B, S, 3, H, Dh), 2, 0, 3, 1, 4)
        q, k, v = (qkv[0], qkv[1], qkv[2])
        scores = torch.einsum('bhqd,bhkd->bhqk', q, k) * Dh ** (-0.5)
        idx = torch.arange(S)
        mask = (idx[:, None] - idx[None, :] >= 0) & (idx[:, None] - idx[None, :] < W)
        scores = torch.where(mask[None, None], scores, -1000000000.0)
        p = _softmax(scores, axis=-1)
        o = torch.einsum('bhqk,bhkd->bhqd', p, v)
        return (lambda x, *d: x.permute(*d))(o, 0, 2, 1, 3).reshape(B, S, D) @ wo

    def _B_ref(x, mem0, Wq, Wk, Wv, Wo, seg_len):
        B, S, Dm = x.shape
        H, Dh = (Wq.shape[1], Wq.shape[2])
        M = mem0.shape[1]
        scale = Dh ** (-0.5)
        n_seg = S // seg_len
        L = M + seg_len
        idx = torch.arange(L)
        mask = (idx[:, None] < M) | (idx[:, None] >= idx[None, :])
        mem = mem0
        outs = []
        for s in range(n_seg):
            xs = x[:, s * seg_len:(s + 1) * seg_len, :].clone()
            h = torch.concatenate([mem, xs], axis=1)
            q = torch.einsum('btd,dhe->bhte', h, Wq)
            k = torch.einsum('btd,dhe->bhte', h, Wk)
            v = torch.einsum('btd,dhe->bhte', h, Wv)
            scores = torch.einsum('bhqe,bhke->bhqk', q, k) * scale
            scores = torch.where(mask[None, None], scores, -1000000000.0)
            p = _softmax(scores, axis=-1)
            o = torch.einsum('bhqk,bhke->bhqe', p, v)
            o = torch.einsum('bhte,hed->btd', o, Wo)
            mem = o[:, :M, :].clone()
            outs.append(o[:, M:, :])
        return torch.concatenate(outs, axis=1)
    a = _A_ref(A_x, A_wqkv, A_wo)
    b = _B_ref(B_x, B_mem0, B_Wq, B_Wk, B_Wv, B_Wo, B_seg_len)
    return torch.concatenate([a, b], axis=-1)
```

```cpp
#include <cuda_runtime.h>
#include <cuda_bf16.h>
#include <cuda.h>
#include <stdint.h>

#define DEVI __device__ __forceinline__

DEVI uint32_t smem_u32(const void* p) { return (uint32_t)__cvta_generic_to_shared(p); }
DEVI uint32_t mapa(uint32_t a, uint32_t r) { uint32_t o; asm("mapa.shared::cluster.u32 %0, %1, %2;" : "=r"(o) : "r"(a), "r"(r)); return o; }
DEVI void mbar_init(uint32_t bar, uint32_t cnt) { asm volatile("mbarrier.init.shared::cta.b64 [%0], %1;" :: "r"(bar), "r"(cnt) : "memory"); }
DEVI void mbar_arrive(uint32_t bar) { asm volatile("mbarrier.arrive.shared::cta.b64 _, [%0];" :: "r"(bar) : "memory"); }
DEVI void mbar_arrive_tx(uint32_t bar, uint32_t bytes) { asm volatile("mbarrier.arrive.expect_tx.shared::cta.b64 _, [%0], %1;" :: "r"(bar), "r"(bytes) : "memory"); }
DEVI void mbar_arrive_remote(uint32_t rbar) { asm volatile("mbarrier.arrive.shared::cluster.b64 _, [%0];" :: "r"(rbar) : "memory"); }
DEVI void mbar_wait(uint32_t bar, uint32_t parity) {
  asm volatile("{\n.reg .pred p;\n.reg .u32 c;\nmov.u32 c, 0;\n"
               "W_%=:\nmbarrier.try_wait.parity.shared::cta.b64 p, [%0], %1;\n@p bra D_%=;\n"
               "add.u32 c, c, 1;\nsetp.lt.u32 p, c, 400000;\n@p bra W_%=;\ntrap;\nD_%=:\n}"
               :: "r"(bar), "r"(parity) : "memory");
}
DEVI void mbar_spin(uint32_t bar, uint32_t parity) {
  asm volatile("{\n.reg .pred p;\nW_%=:\nmbarrier.try_wait.parity.shared::cta.b64 p, [%0], %1;\n@!p bra W_%=;\n}" :: "r"(bar), "r"(parity) : "memory");
}
DEVI void mbar_wait_cluster(uint32_t bar, uint32_t parity) {
  asm volatile("{\n.reg .pred p;\n.reg .u32 c;\nmov.u32 c, 0;\n"
               "W_%=:\nmbarrier.try_wait.parity.acquire.cluster.shared::cta.b64 p, [%0], %1;\n@p bra D_%=;\n"
               "add.u32 c, c, 1;\nsetp.lt.u32 p, c, 400000;\n@p bra W_%=;\ntrap;\nD_%=:\n}"
               :: "r"(bar), "r"(parity) : "memory");
}
DEVI void tma_load_2d(uint32_t dst, const CUtensorMap* tm, int c0, int c1, uint32_t bar) {
  asm volatile("cp.async.bulk.tensor.2d.shared::cluster.global.mbarrier::complete_tx::bytes [%0], [%1, {%3, %4}], [%2];"
               :: "r"(dst), "l"(tm), "r"(bar), "r"(c0), "r"(c1) : "memory");
}
DEVI void tma_prefetch_2d(const CUtensorMap* tm, int c0, int c1) {
  asm volatile("cp.async.bulk.prefetch.tensor.2d.L2.global [%0, {%1, %2}];" :: "l"(tm), "r"(c0), "r"(c1) : "memory");
}
DEVI void tma_store_2d(const CUtensorMap* tm, uint32_t src, int c0, int c1) {
  asm volatile("cp.async.bulk.tensor.2d.global.shared::cta.bulk_group [%0, {%2, %3}], [%1];" :: "l"(tm), "r"(src), "r"(c0), "r"(c1) : "memory");
}
DEVI void bulk_load(uint32_t dst, const void* src, uint32_t bytes, uint32_t bar) {
  asm volatile("cp.async.bulk.shared::cluster.global.mbarrier::complete_tx::bytes [%0], [%1], %2, [%3];" :: "r"(dst), "l"(src), "r"(bytes), "r"(bar) : "memory");
}
DEVI void bulk_s2s(uint32_t rdst, uint32_t src, uint32_t bytes, uint32_t rbar) {
  asm volatile("cp.async.bulk.shared::cluster.shared::cta.mbarrier::complete_tx::bytes [%0], [%1], %2, [%3];" :: "r"(rdst), "r"(src), "r"(bytes), "r"(rbar) : "memory");
}
DEVI void bulk_store(void* dst, uint32_t src, uint32_t bytes) {
  asm volatile("cp.async.bulk.global.shared::cta.bulk_group [%0], [%1], %2;" :: "l"(dst), "r"(src), "r"(bytes) : "memory");
}
DEVI void fence_proxy_async() { asm volatile("fence.proxy.async.shared::cta;" ::: "memory"); }
#define BAR_SYNC(id, n) asm volatile("bar.sync %0, %1;" :: "n"(id), "n"(n) : "memory")
#define WG_FENCE() asm volatile("wgmma.fence.sync.aligned;" ::: "memory")
#define WG_COMMIT() asm volatile("wgmma.commit_group.sync.aligned;" ::: "memory")
#define WG_WAIT(n) asm volatile("wgmma.wait_group.sync.aligned %0;" :: "n"(n) : "memory")

template <int N> DEVI void acc_fence(float* d) {
#pragma unroll
  for (int i = 0; i < N; i++) asm volatile("" : "+f"(d[i]) :: "memory");
}
DEVI uint64_t mkdesc(uint32_t saddr, uint32_t lbo, uint32_t sbo, uint32_t swz) {
  uint32_t lo = ((saddr & 0x3FFFF) >> 4) | ((lbo >> 4) << 16);
  uint32_t hi = (sbo >> 4) | (swz << 30);
  return ((uint64_t)hi << 32) | lo;
}
DEVI void ldsm4(uint32_t* r, uint32_t addr) {
  asm volatile("ldmatrix.sync.aligned.m8n8.x4.shared.b16 {%0,%1,%2,%3}, [%4];" : "=r"(r[0]), "=r"(r[1]), "=r"(r[2]), "=r"(r[3]) : "r"(addr) : "memory");
}
DEVI void ldsm2(uint32_t* r, uint32_t addr) {
  asm volatile("ldmatrix.sync.aligned.m8n8.x2.shared.b16 {%0,%1}, [%2];" : "=r"(r[0]), "=r"(r[1]) : "r"(addr) : "memory");
}
DEVI void ldsm4t(uint32_t* r, uint32_t addr) {
  asm volatile("ldmatrix.sync.aligned.m8n8.x4.trans.shared.b16 {%0,%1,%2,%3}, [%4];" : "=r"(r[0]), "=r"(r[1]), "=r"(r[2]), "=r"(r[3]) : "r"(addr) : "memory");
}
DEVI void mma16816(float* d, uint32_t a0, uint32_t a1, uint32_t a2, uint32_t a3, uint32_t b0, uint32_t b1) {
  asm volatile("mma.sync.aligned.m16n8k16.row.col.f32.bf16.bf16.f32 {%0,%1,%2,%3}, {%4,%5,%6,%7}, {%8,%9}, {%0,%1,%2,%3};"
               : "+f"(d[0]), "+f"(d[1]), "+f"(d[2]), "+f"(d[3]) : "r"(a0), "r"(a1), "r"(a2), "r"(a3), "r"(b0), "r"(b1));
}
DEVI void mma16816z(float* d, const uint32_t* a, uint32_t b0, uint32_t b1) {
  asm volatile("mma.sync.aligned.m16n8k16.row.col.f32.bf16.bf16.f32 {%0,%1,%2,%3}, {%4,%5,%6,%7}, {%8,%9}, {%10,%10,%10,%10};"
               : "=f"(d[0]), "=f"(d[1]), "=f"(d[2]), "=f"(d[3]) : "r"(a[0]), "r"(a[1]), "r"(a[2]), "r"(a[3]), "r"(b0), "r"(b1), "f"(0.f));
}
DEVI void mma16816v(float* d, const uint32_t* a, uint32_t b0, uint32_t b1) { mma16816(d, a[0], a[1], a[2], a[3], b0, b1); }
DEVI void mma1688(float* d, uint32_t a0, uint32_t a1, uint32_t b0) {
  asm volatile("mma.sync.aligned.m16n8k8.row.col.f32.bf16.bf16.f32 {%0,%1,%2,%3}, {%4,%5}, {%6}, {%0,%1,%2,%3};"
               : "+f"(d[0]), "+f"(d[1]), "+f"(d[2]), "+f"(d[3]) : "r"(a0), "r"(a1), "r"(b0));
}
DEVI void mbar_arrive_if(bool p, uint32_t bar) { asm volatile("{.reg .pred p; setp.ne.u32 p, %1, 0; @p mbarrier.arrive.shared::cta.b64 _, [%0];}" :: "r"(bar), "r"((uint32_t)p) : "memory"); }
DEVI void mbar_arrive_tx_if(bool p, uint32_t bar, uint32_t bytes) { asm volatile("{.reg .pred p; setp.ne.u32 p, %1, 0; @p mbarrier.arrive.expect_tx.shared::cta.b64 _, [%0], %2;}" :: "r"(bar), "r"((uint32_t)p), "r"(bytes) : "memory"); }
DEVI void mbar_arrive_remote_if(bool p, uint32_t rbar) { asm volatile("{.reg .pred p; setp.ne.u32 p, %1, 0; @p mbarrier.arrive.shared::cluster.b64 _, [%0];}" :: "r"(rbar), "r"((uint32_t)p) : "memory"); }
DEVI uint32_t mbar_try(uint32_t bar, uint32_t parity) {
  uint32_t ok; asm volatile("{.reg .pred p; mbarrier.try_wait.parity.shared::cta.b64 p, [%1], %2; selp.u32 %0, 1, 0, p;}" : "=r"(ok) : "r"(bar), "r"(parity) : "memory"); return ok;
}
DEVI uint32_t mbar_test(uint32_t bar, uint32_t parity) {
  uint32_t ok; asm volatile("{.reg .pred p; mbarrier.test_wait.parity.shared::cta.b64 p, [%1], %2; selp.u32 %0, 1, 0, p;}" : "=r"(ok) : "r"(bar), "r"(parity) : "memory"); return ok;
}
DEVI uint32_t lds32(uint32_t a) { uint32_t v; asm volatile("ld.shared.u32 %0, [%1];" : "=r"(v) : "r"(a) : "memory"); return v; }
#define LIKELY(x) __builtin_expect(!!(x), 1)
#define UNLIKELY(x) __builtin_expect(!!(x), 0)
#define PIN(x) asm volatile("" : "+r"(x))
DEVI uint32_t pack_bf16(float lo, float hi) { uint32_t r; asm("cvt.rn.bf16x2.f32 %0, %1, %2;" : "=r"(r) : "f"(hi), "f"(lo)); return r; }
DEVI float ex2f(float x) { float y; asm("ex2.approx.ftz.f32 %0, %1;" : "=f"(y) : "f"(x)); return y; }
DEVI float rcpf(float x) { float y; asm("rcp.approx.ftz.f32 %0, %1;" : "=f"(y) : "f"(x)); return y; }
DEVI void sts32(uint32_t a, uint32_t v) { asm volatile("st.shared.u32 [%0], %1;" :: "r"(a), "r"(v) : "memory"); }
DEVI void sts64(uint32_t a, uint32_t x, uint32_t y) { asm volatile("st.shared.v2.u32 [%0], {%1,%2};" :: "r"(a), "r"(x), "r"(y) : "memory"); }
DEVI void sts128(uint32_t a, uint32_t x, uint32_t y, uint32_t z, uint32_t w) { asm volatile("st.shared.v4.u32 [%0], {%1,%2,%3,%4};" :: "r"(a), "r"(x), "r"(y), "r"(z), "r"(w) : "memory"); }
DEVI void lds64f(float& x, float& y, uint32_t a) { asm volatile("ld.shared.v2.f32 {%0,%1}, [%2];" : "=f"(x), "=f"(y) : "r"(a) : "memory"); }
DEVI void lds128(uint32_t* r, uint32_t a) { asm volatile("ld.shared.v4.u32 {%0,%1,%2,%3}, [%4];" : "=r"(r[0]), "=r"(r[1]), "=r"(r[2]), "=r"(r[3]) : "r"(a) : "memory"); }
DEVI void st_async32(uint32_t a, uint32_t v, uint32_t bar) { asm volatile("st.async.shared::cluster.mbarrier::complete_tx::bytes.u32 [%0], %1, [%2];" :: "r"(a), "r"(v), "r"(bar) : "memory"); }
DEVI void st_async64(uint32_t a, uint32_t x, uint32_t y, uint32_t bar) { asm volatile("st.async.shared::cluster.mbarrier::complete_tx::bytes.v2.u32 [%0], {%1,%2}, [%3];" :: "r"(a), "r"(x), "r"(y), "r"(bar) : "memory"); }
DEVI void st_async128(uint32_t a, uint32_t x, uint32_t y, uint32_t z, uint32_t w, uint32_t bar) {
  asm volatile("st.async.shared::cluster.mbarrier::complete_tx::bytes.v4.u32 [%0], {%1,%2,%3,%4}, [%5];" :: "r"(a), "r"(x), "r"(y), "r"(z), "r"(w), "r"(bar) : "memory");
}
DEVI uint4 ldg128_relaxed(const void* p) { uint4 v; asm volatile("ld.relaxed.gpu.global.v4.u32 {%0,%1,%2,%3}, [%4];" : "=r"(v.x), "=r"(v.y), "=r"(v.z), "=r"(v.w) : "l"(p) : "memory"); return v; }
DEVI void stg64_relaxed(void* p, uint32_t x, uint32_t y) {
  asm volatile("{.reg .b64 t; mov.b64 t, {%1,%2}; st.relaxed.gpu.global.b64 [%0], t;}" :: "l"(p), "r"(x), "r"(y) : "memory");
}
DEVI void stg32_relaxed(void* p, uint32_t x) { asm volatile("st.relaxed.gpu.global.u32 [%0], %1;" :: "l"(p), "r"(x) : "memory"); }
DEVI void cp_async16(uint32_t dst, const void* src) { asm volatile("cp.async.cg.shared.global [%0], [%1], 16;" :: "r"(dst), "l"(src) : "memory"); }
DEVI uint32_t clk32() { uint32_t c; asm volatile("{.reg .u64 t; mov.u64 t, %%clock64; cvt.u32.u64 %0, t;}" : "=r"(c) :: "memory"); return c; }
DEVI uint32_t gtime() { uint32_t g; asm volatile("mov.u32 %0, %%globaltimer_lo;" : "=r"(g) :: "memory"); return g; }
DEVI int cluster_id() { int v; asm volatile("mov.u32 %0, %%clusterid.x;" : "=r"(v)); return v; }
DEVI int cluster_rank() { int v; asm volatile("mov.u32 %0, %%cluster_ctarank;" : "=r"(v)); return v; }
DEVI bool elect_one() { uint32_t p; asm volatile("{.reg .pred p; elect.sync _|p, 0xffffffff; selp.u32 %0, 1, 0, p;}" : "=r"(p)); return p; }

typedef CUresult (*PFN_encodeTiled)(CUtensorMap*, CUtensorMapDataType, cuuint32_t, void*, const cuuint64_t*, const cuuint64_t*, const cuuint32_t*, const cuuint32_t*,
                                    CUtensorMapInterleave, CUtensorMapSwizzle, CUtensorMapL2promotion, CUtensorMapFloatOOBfill);
static inline PFN_encodeTiled get_encode() {
  static PFN_encodeTiled fn = nullptr;
  if (!fn) { void* p = nullptr; cudaDriverEntryPointQueryResult q; cudaGetDriverEntryPoint("cuTensorMapEncodeTiled", &p, cudaEnableDefault, &q); fn = (PFN_encodeTiled)p; }
  return fn;
}
static inline CUtensorMap make_map(const void* ptr, uint64_t rows, uint64_t cols, uint64_t ld, uint32_t brows, uint32_t bcols, CUtensorMapSwizzle swz, CUtensorMapL2promotion promo = CU_TENSOR_MAP_L2_PROMOTION_L2_256B) {
  CUtensorMap m; cuuint64_t dims[2] = {cols, rows}; cuuint64_t strides[1] = {ld * 2}; cuuint32_t box[2] = {bcols, brows}; cuuint32_t es[2] = {1, 1};
  get_encode()(&m, CU_TENSOR_MAP_DATA_TYPE_BFLOAT16, 2, (void*)ptr, dims, strides, box, es, CU_TENSOR_MAP_INTERLEAVE_NONE, swz, promo, CU_TENSOR_MAP_FLOAT_OOB_FILL_NONE);
  return m;
}
DEVI void wg_ss256_tb(float* d, uint64_t a, uint64_t b, int sd) {
  asm volatile("{.reg .pred p; setp.ne.b32 p, %130, 0; wgmma.mma_async.sync.aligned.m64n256k16.f32.bf16.bf16 {%0,%1,%2,%3,%4,%5,%6,%7,%8,%9,%10,%11,%12,%13,%14,%15,%16,%17,%18,%19,%20,%21,%22,%23,%24,%25,%26,%27,%28,%29,%30,%31,%32,%33,%34,%35,%36,%37,%38,%39,%40,%41,%42,%43,%44,%45,%46,%47,%48,%49,%50,%51,%52,%53,%54,%55,%56,%57,%58,%59,%60,%61,%62,%63,%64,%65,%66,%67,%68,%69,%70,%71,%72,%73,%74,%75,%76,%77,%78,%79,%80,%81,%82,%83,%84,%85,%86,%87,%88,%89,%90,%91,%92,%93,%94,%95,%96,%97,%98,%99,%100,%101,%102,%103,%104,%105,%106,%107,%108,%109,%110,%111,%112,%113,%114,%115,%116,%117,%118,%119,%120,%121,%122,%123,%124,%125,%126,%127}, %128, %129, p, 1, 1, 0, 1;}"
    : "+f"(d[0]), "+f"(d[1]), "+f"(d[2]), "+f"(d[3]), "+f"(d[4]), "+f"(d[5]), "+f"(d[6]), "+f"(d[7]), "+f"(d[8]), "+f"(d[9]), "+f"(d[10]), "+f"(d[11]), "+f"(d[12]), "+f"(d[13]), "+f"(d[14]), "+f"(d[15]), "+f"(d[16]), "+f"(d[17]), "+f"(d[18]), "+f"(d[19]), "+f"(d[20]), "+f"(d[21]), "+f"(d[22]), "+f"(d[23]), "+f"(d[24]), "+f"(d[25]), "+f"(d[26]), "+f"(d[27]), "+f"(d[28]), "+f"(d[29]), "+f"(d[30]), "+f"(d[31]), "+f"(d[32]), "+f"(d[33]), "+f"(d[34]), "+f"(d[35]), "+f"(d[36]), "+f"(d[37]), "+f"(d[38]), "+f"(d[39]), "+f"(d[40]), "+f"(d[41]), "+f"(d[42]), "+f"(d[43]), "+f"(d[44]), "+f"(d[45]), "+f"(d[46]), "+f"(d[47]), "+f"(d[48]), "+f"(d[49]), "+f"(d[50]), "+f"(d[51]), "+f"(d[52]), "+f"(d[53]), "+f"(d[54]), "+f"(d[55]), "+f"(d[56]), "+f"(d[57]), "+f"(d[58]), "+f"(d[59]), "+f"(d[60]), "+f"(d[61]), "+f"(d[62]), "+f"(d[63]), "+f"(d[64]), "+f"(d[65]), "+f"(d[66]), "+f"(d[67]), "+f"(d[68]), "+f"(d[69]), "+f"(d[70]), "+f"(d[71]), "+f"(d[72]), "+f"(d[73]), "+f"(d[74]), "+f"(d[75]), "+f"(d[76]), "+f"(d[77]), "+f"(d[78]), "+f"(d[79]), "+f"(d[80]), "+f"(d[81]), "+f"(d[82]), "+f"(d[83]), "+f"(d[84]), "+f"(d[85]), "+f"(d[86]), "+f"(d[87]), "+f"(d[88]), "+f"(d[89]), "+f"(d[90]), "+f"(d[91]), "+f"(d[92]), "+f"(d[93]), "+f"(d[94]), "+f"(d[95]), "+f"(d[96]), "+f"(d[97]), "+f"(d[98]), "+f"(d[99]), "+f"(d[100]), "+f"(d[101]), "+f"(d[102]), "+f"(d[103]), "+f"(d[104]), "+f"(d[105]), "+f"(d[106]), "+f"(d[107]), "+f"(d[108]), "+f"(d[109]), "+f"(d[110]), "+f"(d[111]), "+f"(d[112]), "+f"(d[113]), "+f"(d[114]), "+f"(d[115]), "+f"(d[116]), "+f"(d[117]), "+f"(d[118]), "+f"(d[119]), "+f"(d[120]), "+f"(d[121]), "+f"(d[122]), "+f"(d[123]), "+f"(d[124]), "+f"(d[125]), "+f"(d[126]), "+f"(d[127])
    : "l"(a), "l"(b), "r"(sd));
}
DEVI void wg_ss64_tb(float* d, uint64_t a, uint64_t b, int sd) {
  asm volatile("{.reg .pred p; setp.ne.b32 p, %34, 0; wgmma.mma_async.sync.aligned.m64n64k16.f32.bf16.bf16 {%0,%1,%2,%3,%4,%5,%6,%7,%8,%9,%10,%11,%12,%13,%14,%15,%16,%17,%18,%19,%20,%21,%22,%23,%24,%25,%26,%27,%28,%29,%30,%31}, %32, %33, p, 1, 1, 0, 1;}"
    : "+f"(d[0]), "+f"(d[1]), "+f"(d[2]), "+f"(d[3]), "+f"(d[4]), "+f"(d[5]), "+f"(d[6]), "+f"(d[7]), "+f"(d[8]), "+f"(d[9]), "+f"(d[10]), "+f"(d[11]), "+f"(d[12]), "+f"(d[13]), "+f"(d[14]), "+f"(d[15]), "+f"(d[16]), "+f"(d[17]), "+f"(d[18]), "+f"(d[19]), "+f"(d[20]), "+f"(d[21]), "+f"(d[22]), "+f"(d[23]), "+f"(d[24]), "+f"(d[25]), "+f"(d[26]), "+f"(d[27]), "+f"(d[28]), "+f"(d[29]), "+f"(d[30]), "+f"(d[31])
    : "l"(a), "l"(b), "r"(sd));
}
DEVI void wg_ss160(float* d, uint64_t a, uint64_t b, int sd) {
  asm volatile("{.reg .pred p; setp.ne.b32 p, %82, 0; wgmma.mma_async.sync.aligned.m64n160k16.f32.bf16.bf16 {%0,%1,%2,%3,%4,%5,%6,%7,%8,%9,%10,%11,%12,%13,%14,%15,%16,%17,%18,%19,%20,%21,%22,%23,%24,%25,%26,%27,%28,%29,%30,%31,%32,%33,%34,%35,%36,%37,%38,%39,%40,%41,%42,%43,%44,%45,%46,%47,%48,%49,%50,%51,%52,%53,%54,%55,%56,%57,%58,%59,%60,%61,%62,%63,%64,%65,%66,%67,%68,%69,%70,%71,%72,%73,%74,%75,%76,%77,%78,%79}, %80, %81, p, 1, 1, 0, 0;}"
    : "+f"(d[0]), "+f"(d[1]), "+f"(d[2]), "+f"(d[3]), "+f"(d[4]), "+f"(d[5]), "+f"(d[6]), "+f"(d[7]), "+f"(d[8]), "+f"(d[9]), "+f"(d[10]), "+f"(d[11]), "+f"(d[12]), "+f"(d[13]), "+f"(d[14]), "+f"(d[15]), "+f"(d[16]), "+f"(d[17]), "+f"(d[18]), "+f"(d[19]), "+f"(d[20]), "+f"(d[21]), "+f"(d[22]), "+f"(d[23]), "+f"(d[24]), "+f"(d[25]), "+f"(d[26]), "+f"(d[27]), "+f"(d[28]), "+f"(d[29]), "+f"(d[30]), "+f"(d[31]), "+f"(d[32]), "+f"(d[33]), "+f"(d[34]), "+f"(d[35]), "+f"(d[36]), "+f"(d[37]), "+f"(d[38]), "+f"(d[39]), "+f"(d[40]), "+f"(d[41]), "+f"(d[42]), "+f"(d[43]), "+f"(d[44]), "+f"(d[45]), "+f"(d[46]), "+f"(d[47]), "+f"(d[48]), "+f"(d[49]), "+f"(d[50]), "+f"(d[51]), "+f"(d[52]), "+f"(d[53]), "+f"(d[54]), "+f"(d[55]), "+f"(d[56]), "+f"(d[57]), "+f"(d[58]), "+f"(d[59]), "+f"(d[60]), "+f"(d[61]), "+f"(d[62]), "+f"(d[63]), "+f"(d[64]), "+f"(d[65]), "+f"(d[66]), "+f"(d[67]), "+f"(d[68]), "+f"(d[69]), "+f"(d[70]), "+f"(d[71]), "+f"(d[72]), "+f"(d[73]), "+f"(d[74]), "+f"(d[75]), "+f"(d[76]), "+f"(d[77]), "+f"(d[78]), "+f"(d[79])
    : "l"(a), "l"(b), "r"(sd));
}
DEVI void wg_rs32_tb(float* d, uint32_t a0, uint32_t a1, uint32_t a2, uint32_t a3, uint64_t b, int sd) {
  asm volatile("{.reg .pred p; setp.ne.b32 p, %21, 0; wgmma.mma_async.sync.aligned.m64n32k16.f32.bf16.bf16 {%0,%1,%2,%3,%4,%5,%6,%7,%8,%9,%10,%11,%12,%13,%14,%15}, {%16,%17,%18,%19}, %20, p, 1, 1, 1;}"
    : "+f"(d[0]), "+f"(d[1]), "+f"(d[2]), "+f"(d[3]), "+f"(d[4]), "+f"(d[5]), "+f"(d[6]), "+f"(d[7]), "+f"(d[8]), "+f"(d[9]), "+f"(d[10]), "+f"(d[11]), "+f"(d[12]), "+f"(d[13]), "+f"(d[14]), "+f"(d[15])
    : "r"(a0), "r"(a1), "r"(a2), "r"(a3), "l"(b), "r"(sd));
}
DEVI void wg_ss128_tb(float* d, uint64_t a, uint64_t b, int sd) {
  asm volatile("{.reg .pred p; setp.ne.b32 p, %66, 0; wgmma.mma_async.sync.aligned.m64n128k16.f32.bf16.bf16 {%0,%1,%2,%3,%4,%5,%6,%7,%8,%9,%10,%11,%12,%13,%14,%15,%16,%17,%18,%19,%20,%21,%22,%23,%24,%25,%26,%27,%28,%29,%30,%31,%32,%33,%34,%35,%36,%37,%38,%39,%40,%41,%42,%43,%44,%45,%46,%47,%48,%49,%50,%51,%52,%53,%54,%55,%56,%57,%58,%59,%60,%61,%62,%63}, %64, %65, p, 1, 1, 0, 1;}"
    : "+f"(d[0]), "+f"(d[1]), "+f"(d[2]), "+f"(d[3]), "+f"(d[4]), "+f"(d[5]), "+f"(d[6]), "+f"(d[7]), "+f"(d[8]), "+f"(d[9]), "+f"(d[10]), "+f"(d[11]), "+f"(d[12]), "+f"(d[13]), "+f"(d[14]), "+f"(d[15]), "+f"(d[16]), "+f"(d[17]), "+f"(d[18]), "+f"(d[19]), "+f"(d[20]), "+f"(d[21]), "+f"(d[22]), "+f"(d[23]), "+f"(d[24]), "+f"(d[25]), "+f"(d[26]), "+f"(d[27]), "+f"(d[28]), "+f"(d[29]), "+f"(d[30]), "+f"(d[31]), "+f"(d[32]), "+f"(d[33]), "+f"(d[34]), "+f"(d[35]), "+f"(d[36]), "+f"(d[37]), "+f"(d[38]), "+f"(d[39]), "+f"(d[40]), "+f"(d[41]), "+f"(d[42]), "+f"(d[43]), "+f"(d[44]), "+f"(d[45]), "+f"(d[46]), "+f"(d[47]), "+f"(d[48]), "+f"(d[49]), "+f"(d[50]), "+f"(d[51]), "+f"(d[52]), "+f"(d[53]), "+f"(d[54]), "+f"(d[55]), "+f"(d[56]), "+f"(d[57]), "+f"(d[58]), "+f"(d[59]), "+f"(d[60]), "+f"(d[61]), "+f"(d[62]), "+f"(d[63])
    : "l"(a), "l"(b), "r"(sd));
}
DEVI void wg_ss32_tb(float* d, uint64_t a, uint64_t b, int sd) {
  asm volatile("{.reg .pred p; setp.ne.b32 p, %18, 0; wgmma.mma_async.sync.aligned.m64n32k16.f32.bf16.bf16 {%0,%1,%2,%3,%4,%5,%6,%7,%8,%9,%10,%11,%12,%13,%14,%15}, %16, %17, p, 1, 1, 0, 1;}"
    : "+f"(d[0]), "+f"(d[1]), "+f"(d[2]), "+f"(d[3]), "+f"(d[4]), "+f"(d[5]), "+f"(d[6]), "+f"(d[7]), "+f"(d[8]), "+f"(d[9]), "+f"(d[10]), "+f"(d[11]), "+f"(d[12]), "+f"(d[13]), "+f"(d[14]), "+f"(d[15])
    : "l"(a), "l"(b), "r"(sd));
}

#define G2LA 4
#define G1CH 2
#define SFENCE 0
#define SCHED_FENCE() asm volatile("{.reg .pred p; setp.eq.s32 p, %0, 1000; @p trap;}" :: "r"(s) : "memory")
#define NORETRY 0
#define KVAT 0
#define PINQ 1
#define SSEAT 10
#define HOLD 5
#define EXPT 0
#define EARLYLA 4
#define PHBAR 1
namespace rk {
constexpr int NRF = 48;
constexpr int NSS = 64 - NRF;
constexpr uint32_t SB0 = 1024;
constexpr uint32_t OFF_W = 0;
constexpr uint32_t OFF_RING = OFF_W + 2 * NSS * 2048;
constexpr uint32_t OFF_WO = OFF_RING + 4 * 4096 + 4 * 5120;
constexpr uint32_t OFF_MEM = OFF_WO + 22 * 4096;
constexpr uint32_t OFF_KX = OFF_MEM + 12288;
constexpr uint32_t OFF_VX = OFF_KX + 8192;
constexpr uint32_t OFF_QM = OFF_VX + 8192;
constexpr uint32_t OFF_O = OFF_QM + 3 * 2048;
constexpr uint32_t OFF_S = OFF_O + 2048;
constexpr uint32_t OFF_BAR = OFF_S + 1536;
constexpr uint32_t B_FULL = OFF_BAR, B_EMPTY = B_FULL + 64, B_MEM = B_EMPTY + 64, B_SIG = B_MEM + 24, B_QKV = B_SIG + 24,
                   B_XFULL = B_QKV + 8, B_XAV = B_XFULL + 8, B_WFULL = B_XAV + 8, B_WEMPTY = B_WFULL + 40, B_WSS = B_WEMPTY + 40,
                   B_WO = B_WSS + 8, B_XRDY = B_WO + 8, B_MLD = B_XRDY + 8, B_PLD = B_MLD + 24, B_RTR = B_PLD + 24, B_OF = B_RTR + 24, B_SSE = B_OF + 8, B_REF = B_SSE + 8, B_GO = B_REF + 8, OFF_LATE = B_GO + 8, OFF_TIM = OFF_LATE + 8;
constexpr uint32_t SMEM_BYTES = OFF_TIM + 128;
static_assert(SMEM_BYTES <= 232448, "smem");
__host__ __device__ constexpr uint32_t ring_off(int sl) { return OFF_RING + (sl < 4 ? sl * 4096 : 16384 + (sl - 4) * 5120); }
}

__device__ __align__(256) uint32_t g_part[72 * 32 * 64];
__device__ __align__(256) uint4 g_mem[4 * 1024];
__device__ __align__(256) uint4 g_img[64 * 32 * 3 * 512];
__device__ uint32_t g_imgm[64 * 32 * 2 * 512];
__device__ __align__(128) uint32_t g_ts[96];
__device__ __align__(256) uint32_t g_rflag[64];
#define PSTAMP(i)
#define TSTAMP(i)
#define TSTAMPW(i, w)
#define GSTAMP(i)
#define TVAL(i, v)
#define TDUMP(mask, st)

#define ACC16(d) "+f"(d[0]), "+f"(d[1]), "+f"(d[2]), "+f"(d[3]), "+f"(d[4]), "+f"(d[5]), "+f"(d[6]), "+f"(d[7]), "+f"(d[8]), "+f"(d[9]), "+f"(d[10]), "+f"(d[11]), "+f"(d[12]), "+f"(d[13]), "+f"(d[14]), "+f"(d[15])
template <int SCALE_D> DEVI void wg_rs32(float* d, const uint32_t* a, uint64_t b) {
  asm volatile("wgmma.mma_async.sync.aligned.m64n32k16.f32.bf16.bf16 {%0,%1,%2,%3,%4,%5,%6,%7,%8,%9,%10,%11,%12,%13,%14,%15}, {%16,%17,%18,%19}, %20, %21, 1, 1, 0;"
               : ACC16(d) : "r"(a[0]), "r"(a[1]), "r"(a[2]), "r"(a[3]), "l"(b), "n"(SCALE_D));
}
DEVI void wg_ss40(float* d, uint64_t a, uint64_t b) {
  asm volatile("wgmma.mma_async.sync.aligned.m64n40k16.f32.bf16.bf16 {%0,%1,%2,%3,%4,%5,%6,%7,%8,%9,%10,%11,%12,%13,%14,%15,%16,%17,%18,%19}, %20, %21, 1, 1, 1, 1, 0;"
               : ACC16(d), "+f"(d[16]), "+f"(d[17]), "+f"(d[18]), "+f"(d[19]) : "l"(a), "l"(b));
}
template <int SCALE_D> DEVI void wg_ss8(float* d, uint64_t a, uint64_t b) {
  asm volatile("wgmma.mma_async.sync.aligned.m64n8k16.f32.bf16.bf16 {%0,%1,%2,%3}, %4, %5, %6, 1, 1, 1, 1;"
               : "+f"(d[0]), "+f"(d[1]), "+f"(d[2]), "+f"(d[3]) : "l"(a), "l"(b), "n"(SCALE_D));
}
DEVI uint32_t movmat(uint32_t x) { uint32_t y; asm volatile("movmatrix.sync.aligned.m8n8.trans.b16 %0, %1;" : "=r"(y) : "r"(x)); return y; }
DEVI float tag_round(float v, uint32_t rc) { return __uint_as_float((__float_as_uint(v) + rc) & 0xfffe0000u); }

struct RParams { int c1, c1b, c1c, c2, c2b, c2c, dts; };

DEVI uint32_t ldg32_relaxed(const void* p) { uint32_t v; asm volatile("ld.relaxed.gpu.global.u32 %0, [%1];" : "=r"(v) : "l"(p) : "memory"); return v; }
DEVI void spin_until(uint32_t t) { while ((int)(clk32() - t) < 0) {} }
DEVI void spin_until_ns(uint32_t t) {
#pragma unroll 1
  for (int it = 0; (int)(gtime() - t) < 0 && it < 64; it++) {}
}
DEVI void load_partials(const uint32_t sb, const int cta, const int rho, const CUtensorMap* tmP, const uint32_t bar) {
  const int kst = 24 * rho + (cta >> 2), pslot = rho < 2 ? kst : (kst < 54 ? kst + 2 : (kst < 59 ? kst + 5 : kst + 8));
  asm volatile("{.reg .pred p; elect.sync _|p, 0xffffffff;\n @p mbarrier.arrive.expect_tx.shared::cta.b64 _, [%2], 2048;\n"
               " @p cp.async.bulk.tensor.2d.shared::cluster.global.mbarrier::complete_tx::bytes [%0], [%1, {%3, %4}], [%2];}"
               :: "r"(sb + rk::OFF_QM + rho * 2048), "l"(tmP), "r"(bar), "r"((cta & 3) * 32), "r"(pslot * 32) : "memory");
}
DEVI void stg32_low8(uint8_t* p, uint32_t v, uint32_t la, bool ok) {
  asm volatile("{.reg .pred p, q; .reg .b32 t; setp.ne.u32 q, %3, 0; and.b32 t, %2, 0x300; setp.eq.and.u32 p, t, 0, q; @p st.relaxed.gpu.global.u32 [%0], %1;}"
               :: "l"(p), "r"(v), "r"(la), "r"((uint32_t)ok) : "memory");
}
DEVI bool sum_sector(const uint32_t lj, const uint32_t la, const uint32_t tag, uint8_t* op) {
  uint32_t w[8];
  ldsm4(w, lj); ldsm4(w + 4, lj + 1024);
  uint32_t tg; float y0, y1;
  asm volatile("{.reg .b32 a,b,c,d,e,f,g,h,i,j,k,l,m,n,o,q,u,v,x,y;\n"
               " shl.b32 a, %3, 16; shl.b32 b, %4, 16; lop3.b32 u, %3, %4, %11, 0x7e; and.b32 i, %3, 0xffff0000; and.b32 j, %4, 0xffff0000; add.f32 a, a, b; add.f32 i, i, j;\n"
               " shl.b32 c, %5, 16; shl.b32 d, %6, 16; lop3.b32 v, %5, %6, %11, 0x7e; and.b32 k, %5, 0xffff0000; and.b32 l, %6, 0xffff0000; add.f32 c, c, d; add.f32 k, k, l;\n"
               " shl.b32 e, %7, 16; shl.b32 f, %8, 16; lop3.b32 x, %7, %8, %11, 0x7e; and.b32 m, %7, 0xffff0000; and.b32 n, %8, 0xffff0000; add.f32 e, e, f; add.f32 m, m, n;\n"
               " shl.b32 g, %9, 16; shl.b32 h, %10, 16; lop3.b32 y, %9, %10, %11, 0x7e; and.b32 o, %9, 0xffff0000; and.b32 q, %10, 0xffff0000; add.f32 g, g, h; add.f32 o, o, q;\n"
               " add.f32 a, a, c; add.f32 i, i, k; add.f32 e, e, g; add.f32 m, m, o; lop3.b32 u, u, v, x, 0xfe; add.f32 %0, a, e; add.f32 %1, i, m; or.b32 %2, u, y;}"
               : "=f"(y0), "=f"(y1), "=r"(tg) : "r"(w[0]), "r"(w[4]), "r"(w[1]), "r"(w[5]), "r"(w[2]), "r"(w[6]), "r"(w[3]), "r"(w[7]), "r"(tag));
  y0 = (y0 + __shfl_xor_sync(0xffffffffu, y0, 8)) + (__shfl_xor_sync(0xffffffffu, y0, 16) + __shfl_xor_sync(0xffffffffu, y0, 24));
  y1 = (y1 + __shfl_xor_sync(0xffffffffu, y1, 8)) + (__shfl_xor_sync(0xffffffffu, y1, 16) + __shfl_xor_sync(0xffffffffu, y1, 24));
  const bool bad = __any_sync(0xffffffffu, (tg & 1) && (la & 0x50) == 0) && !NORETRY;
  stg32_low8(op, pack_bf16(y0, y1), la, !bad);
  return bad;
}
DEVI void reducer_warp(const uint32_t sb, const int cta, const int u, const CUtensorMap* tmP) {
  using namespace rk;
  const int lane = threadIdx.x & 31, j = lane & 7;
  const uint32_t la = __shfl_sync(0xffffffffu, sb + OFF_QM + (lane >> 1) * 64 + u * 32 + (lane & 1) * 16, lane);
  const int n = 2 * (cta & 3) + u, kq = cta >> 2;
  const uint32_t o01 = cta * 64 + u * 32 + j * 4;
  const uint32_t o2 = 12288 + (kq >> 2) * 1024 + n * 128 + (((2 * (kq & 3) + (j & 1)) ^ n) << 4) + (j >> 1) * 4;
  const uint32_t oo = __shfl_sync(0xffffffffu, o01 | (o2 << 16), lane);
#pragma unroll 1
  for (int i = 0; i < 4; i++) {
    uint8_t* p = (uint8_t*)g_mem + i * 16384;
    stg32_low8(p + o01, 0xffffffffu, la, true); stg32_low8(p + o01 + 6144, 0xffffffffu, la, true); stg32_low8(p + o2, 0xffffffffu, la, cta < 64);
  }
  uint32_t rph = 0;
#pragma unroll 1
  for (int s = 0; s < 63; s++) {
    const uint32_t par = s & 1, tag = par ^ 1;
    uint32_t o = oo;
    PIN(o);
    uint8_t* p = (uint8_t*)g_mem + (((s + 1) & 3) * 16384 + (o & 0xffff));
    int jb = 0;
    do {
      if (cta < 64) {
        uint8_t* q = (uint8_t*)g_mem + (((s + 1) & 3) * 16384 + (o >> 16));
        asm volatile("" : "+l"(p), "+l"(q));
        mbar_spin(sb + B_PLD + 16, par);
        GSTAMP(28);
        if (sum_sector(la + 4096, la, tag, q)) break;
        GSTAMP(19);
      }
      jb = 1;
      mbar_spin(sb + B_PLD, par);
      GSTAMP(24);
      if (sum_sector(la, la, tag, p)) break;
      GSTAMP(11);
      jb = 2;
      mbar_spin(sb + B_PLD + 8, par);
      GSTAMP(27);
      const bool bad = sum_sector(la + 2048, la, tag, p + 6144);
      mbar_arrive_if(!bad && (la & 0x3d0) == 0, sb + B_MEM + 16);
      if (!bad) jb = 3;
      GSTAMP(15);
    } while (0);
    jb = __shfl_sync(0xffffffffu, jb, 0);
    if (jb < 3) {
      bool again = true;
#pragma unroll 1
      for (; jb < 3; jb++) {
        const int rho = jb == 0 ? 2 : jb - 1;
        uint8_t* op = (uint8_t*)g_mem + (((s + 1) & 3) * 16384 + (jb == 0 ? oo >> 16 : (oo & 0xffff) + rho * 6144));
        mbar_wait(sb + B_PLD + rho * 8, par);
#pragma unroll 1
        for (int tries = 0;; tries++) {
          if (again) {
            load_partials(sb, cta, rho, tmP, sb + B_RTR + u * 8);
            mbar_wait(sb + B_RTR + u * 8, rph); rph ^= 1;
          }
          again = sum_sector(la + rho * 2048, la, tag, op);
          if (!again) break;
          if (tries > 200000) asm volatile("trap;");
        }
      }
      mbar_arrive_if((la & 0x3d0) == 0, sb + B_MEM + 16);
    }
    o = oo;
    PIN(o);
    p = (uint8_t*)g_mem + (s & 3) * 16384;
    stg32_low8(p + (o & 0xffff), 0xffffffffu, la, true); stg32_low8(p + (o & 0xffff) + 6144, 0xffffffffu, la, true);
    stg32_low8(p + (o >> 16), 0xffffffffu, la, cta < 64);
  }
}
template <int RHO> DEVI void fetch_rows(const uint32_t sb, const uint8_t* ms, const uint32_t bar) {
  using namespace rk;
  if (RHO < 2)
    asm volatile("{.reg .pred p; elect.sync _|p, 0xffffffff;\n @p mbarrier.arrive.expect_tx.shared::cta.b64 _, [%2], 6144;\n"
                 " @p cp.async.bulk.shared::cluster.global.mbarrier::complete_tx::bytes [%0], [%1], 6144, [%2];}"
                 :: "r"(sb + OFF_MEM + RHO * 6144), "l"(ms + RHO * 6144), "r"(bar) : "memory");
  else
    asm volatile("{.reg .pred p; elect.sync _|p, 0xffffffff;\n @p mbarrier.arrive.expect_tx.shared::cta.b64 _, [%2], 4096;\n"
                 " @p cp.async.bulk.shared::cluster.global.mbarrier::complete_tx::bytes [%0], [%1], 1024, [%2];\n"
                 " @p cp.async.bulk.shared::cluster.global.mbarrier::complete_tx::bytes [%0+5120], [%1+1024], 1024, [%2];\n"
                 " @p cp.async.bulk.shared::cluster.global.mbarrier::complete_tx::bytes [%0+10240], [%1+2048], 1024, [%2];\n"
                 " @p cp.async.bulk.shared::cluster.global.mbarrier::complete_tx::bytes [%0+15360], [%1+3072], 1024, [%2];}"
                 :: "r"(sb + ring_off(4) + 4096), "l"(ms + 12288), "r"(bar) : "memory");
}
template <int RHO> DEVI bool rows_missing(const uint32_t ca) {
  using namespace rk;
  uint32_t mx = 0;
  if (RHO == 2) {
#pragma unroll
    for (int i = 0; i < 4; i++) mx = max(mx, lds32(ca + ring_off(4) + 4096 + i * 5120));
  } else {
    uint32_t w[12];
#pragma unroll
    for (int i = 0; i < 12; i++) w[i] = lds32(ca + OFF_MEM + i * 1024);
#pragma unroll
    for (int i = 0; i < 6; i++) mx = max(mx, max(w[i], w[i + 6]));
  }
  return __any_sync(0xffffffffu, mx == 0xffffffffu) && !NORETRY;
}
template <int RHO> DEVI void fetch_again(const uint32_t sb, const uint8_t* ms, const uint32_t ca, uint32_t& rph) {
  using namespace rk;
#pragma unroll 1
  for (int it = 0;; it++) {
    if (RHO == 2) fetch_rows<2>(sb, ms, sb + B_RTR + 16);
    else if (elect_one()) { mbar_arrive_tx(sb + B_RTR + 16, 12288); bulk_load(sb + OFF_MEM, ms, 12288, sb + B_RTR + 16); }
    mbar_wait(sb + B_RTR + 16, rph); rph ^= 1;
    if (!rows_missing<RHO>(ca)) break;
    if (it > 200000) asm volatile("trap;");
  }
}
DEVI void fetcher_warp(const uint32_t sb, const int cta, const CUtensorMap* tmP, const RParams& prm) {
  using namespace rk;
  const int lane = threadIdx.x & 31;
  const uint32_t ca = __shfl_sync(0xffffffffu, sb + lane * 32 + (lane >> 2) * 4, lane);
  const bool l0 = ca == sb;
  const int h = cluster_id();
  if (l0) sts32(sb + OFF_LATE, 0xffffffffu);
  if (lane < 6) mbar_arrive(sb + (lane < 2 ? B_MLD + lane * 8 : (lane == 2 ? B_MEM : B_MEM + 16)));
  uint32_t rph = 0;
  bool late = false;
  uint32_t dur = 1152;
#pragma unroll 1
  for (int s = 0; s < 63; s++) {
    const uint32_t par = s & 1, ttag = (s + 1) & 31;
    const uint8_t* ms = (const uint8_t*)g_mem + ((s + 1) & 3) * 16384;
    mbar_wait(sb + (late ? B_QKV : B_REF), par);
    const uint32_t tref = (gtime() - (late ? 448 : 0)) & ~31u;
    if (l0) stg32_relaxed(g_ts + (cta - 3 * h) * 32 + h, (tref << 11) | ((dur >> 1) << 5) | ttag);
    spin_until(clk32() + prm.dts);
    int ts; uint32_t td;
#pragma unroll 1
    for (int it = 0; it < 100000; it++) {
      const uint32_t u = ldg32_relaxed(g_ts + lane), v = ldg32_relaxed(g_ts + 32 + lane), w = ldg32_relaxed(g_ts + 64 + lane);
      ts = max(max((int)(u - (tref << 11)), (int)(v - (tref << 11))), (int)(w - (tref << 11))) >> 16;
      td = max(max(u & 0xffe0u, v & 0xffe0u), w & 0xffe0u);
      if (!__any_sync(0xffffffffu, ((u ^ ttag) | (v ^ ttag) | (w ^ ttag)) & 31)) break;
    }
    uint32_t t0 = tref + __reduce_max_sync(0xffffffffu, ts) * 32 + (__reduce_max_sync(0xffffffffu, td) >> 4) + prm.c1;
    const uint32_t tcl = tref + __shfl_sync(0xffffffffu, ts, h) * 32;
    const bool meas = !mbar_test(sb + B_SIG + 16, par) && !late;
    mbar_wait(sb + B_SIG + 16, par);
    if (meas) dur += min(max((int)(gtime() - tcl - dur), -128), 128) >> 2;
    GSTAMP(18);
    fence_proxy_async();
    spin_until_ns(t0);
    if (cta < 64) load_partials(sb, cta, 2, tmP, sb + B_PLD + 16);
    mbar_spin(sb + B_SIG, par);
    GSTAMP(10);
    spin_until_ns(t0 + prm.c1b);
    load_partials(sb, cta, 0, tmP, sb + B_PLD);
    mbar_spin(sb + B_SIG + 8, par);
    GSTAMP(14);
    spin_until_ns(t0 + prm.c1c);
    load_partials(sb, cta, 1, tmP, sb + B_PLD + 8);
    t0 += prm.c2;
    spin_until_ns(t0);
    fetch_rows<2>(sb, ms, sb + B_MLD + 16);
    GSTAMP(20);
    mbar_spin(sb + B_MLD + 16, par);
    {
      const bool bad = rows_missing<2>(ca);
      mbar_arrive_if(l0 && !bad, sb + B_MEM + 16);
      if (UNLIKELY(bad)) { fetch_again<2>(sb, ms, ca, rph); mbar_arrive_if(l0, sb + B_MEM + 16); t0 = gtime() - 320; }
    }
    GSTAMP(21);
    spin_until_ns(t0 + prm.c2b);
    fetch_rows<0>(sb, ms, sb + B_MLD);
    GSTAMP(12);
    spin_until_ns(t0 + prm.c2c);
    fetch_rows<1>(sb, ms, sb + B_MLD + 8);
    GSTAMP(16);
    mbar_spin(sb + B_MLD, par ^ 1);
    mbar_spin(sb + B_MLD + 8, par ^ 1);
    GSTAMP(13);
    late = rows_missing<0>(ca);
    if (UNLIKELY(late)) { if (l0) sts32(sb + OFF_LATE, s + 1); __syncwarp(); fetch_again<0>(sb, ms, ca, rph); }
    mbar_arrive_if(l0, sb + B_MEM);
    GSTAMP(17);
  }
}

__global__ void __launch_bounds__(384, 1) __cluster_dims__(3, 1, 1)
rec_kernel(const __grid_constant__ CUtensorMap tmWq, const __grid_constant__ CUtensorMap tmWk, const __grid_constant__ CUtensorMap tmWv,
           const __grid_constant__ CUtensorMap tmWo, const __grid_constant__ CUtensorMap tmX, const __grid_constant__ CUtensorMap tmP,
           const __nv_bfloat16* __restrict__ mem0,
           const __nv_bfloat16* __restrict__ wo_ptr, RParams prm) {
  using namespace rk;
  extern __shared__ __align__(1024) uint8_t smem_raw[];
  const uint32_t sb = smem_u32(smem_raw);
  const int tid = threadIdx.x, lane = tid & 31;
  const int warp = __shfl_sync(0xffffffffu, tid >> 5, 0);
  const int cta = blockIdx.x;
  if (tid == 0) {
    if ((sb & 0xffffff) != SB0) asm volatile("trap;");
    for (int i = 0; i < 8; i++) { mbar_init(sb + B_FULL + i * 8, 1); mbar_init(sb + B_EMPTY + i * 8, 2); }
    for (int i = 0; i < 3; i++) { mbar_init(sb + B_MEM + i * 8, i == 2 ? 3 : 1); mbar_init(sb + B_SIG + i * 8, i < 2 ? 8 : (cluster_rank() == 0 ? 6 : 5)); }
    for (int i = 0; i < 9; i++) mbar_init(sb + B_MLD + i * 8, 1);
    mbar_init(sb + B_QKV, 8); mbar_init(sb + B_XFULL, 1); mbar_init(sb + B_XAV, 2); mbar_init(sb + B_OF, 4); mbar_init(sb + B_SSE, 2); mbar_init(sb + B_REF, 2); mbar_init(sb + B_GO, 1);
    for (int i = 0; i < 5; i++) { mbar_init(sb + B_WFULL + i * 8, 1); mbar_init(sb + B_WEMPTY + i * 8, 8); }
    mbar_init(sb + B_WSS, 1); mbar_init(sb + B_WO, 1); mbar_init(sb + B_XRDY, 8);
    asm volatile("fence.mbarrier_init.release.cluster;" ::: "memory");
  }
  if (warp == 0) PSTAMP(0);
  __syncthreads();
  asm volatile("griddepcontrol.launch_dependents;");
  asm volatile("barrier.cluster.arrive.relaxed.aligned;" ::: "memory");

  if (warp >= 8) {
    asm volatile("setmaxnreg.dec.sync.aligned.u32 24;");
    if (warp == 8) {
      const int h = cluster_id(), r = cluster_rank();
      const CUtensorMap* tmW = r == 0 ? &tmWq : (r == 1 ? &tmWk : &tmWv);
      auto load_w = [&](int c) {
        const int sl = c % 5; const uint32_t bar = sb + B_WFULL + sl * 8, dst = sb + OFF_WO + sl * 16384;
        mbar_arrive_tx(bar, 16384);
        tma_load_2d(dst, tmW, h * 128, c * 64, bar);
        tma_load_2d(dst + 8192, tmW, h * 128 + 64, c * 64, bar);
      };
      auto load_x = [&](int sg, int c) {
        mbar_arrive_tx(sb + B_FULL + (c & 7) * 8, 4096);
        tma_load_2d(sb + ring_off(c & 7), &tmX, c * 64, sg * 32, sb + B_FULL + (c & 7) * 8);
      };
      if (elect_one()) {
#pragma unroll
        for (int c = 0; c < 8; c++) { if (c < 5) load_w(c); load_x(0, c); }
        for (int sg = 0; sg < 4; sg++) tma_prefetch_2d(&tmX, (cta & 15) * 64, sg * 32);
      }
#pragma unroll
      for (int c = 0; c < NRF / 4; c++) {
        mbar_wait(sb + B_WEMPTY + (c % 5) * 8, (c / 5) & 1);
        if (elect_one()) {
          if (c + 5 < NRF / 4) load_w(c + 5);
          if (c + 5 == NRF / 4 - 1) {
            mbar_arrive_tx(sb + B_WSS, 2 * NSS * 2048);
#pragma unroll
            for (int i = 0; i < NSS / 2; i++) tma_load_2d(sb + OFF_W + (i & 1) * NSS * 2048 + (i >> 1) * 8192, tmW, h * 128 + (i & 1) * 64, NRF * 16 + (i >> 1) * 64, sb + B_WSS);
            mbar_arrive_tx(sb + B_WO, 22 * 4096);
          }
        }
        if (c >= 1 && c <= 8) { mbar_wait(sb + B_EMPTY + (c - 1) * 8, 0); if (elect_one()) load_x(0, c + 7); }
      }
      asm volatile("barrier.cluster.wait.aligned;" ::: "memory");
      const uint32_t p1 = mapa(sb, r == 2 ? 0 : r + 1), p2 = mapa(sb, r == 0 ? 2 : r - 1);
#pragma unroll 1
      for (int sg = 0; sg < 64; sg++) {
        const uint8_t* kv = (const uint8_t*)g_img + (size_t)(((sg - 1) * 32 + h) * 3 + 1) * 8192;
        auto load_slot = [&](int row, int col, int j) {
          asm volatile("{.reg .pred p; elect.sync _|p, 0xffffffff;\n @p mbarrier.arrive.expect_tx.shared::cta.b64 _, [%2], 4096;\n"
                       " @p cp.async.bulk.tensor.2d.shared::cluster.global.mbarrier::complete_tx::bytes [%0], [%1, {%3, %4}], [%2];}"
                       :: "r"(sb + OFF_RING + j * 4096 + max(j - 4, 0) * 1024), "l"(&tmX), "r"(sb + B_FULL + j * 8), "r"(col), "r"(row) : "memory");
        };
#pragma unroll 1
        for (int j = sg > 0 ? 0 : 8; j < 8; j++) {
          mbar_spin(sb + B_EMPTY + j * 8, sg & 1);
          if (j == 4) TDUMP(0xe2c002ffu, sg - 2);
          load_slot(sg * 32, 512 + j * 64, j);
        }
        if (sg > 0) {
          mbar_wait(sb + B_XAV, (sg - 1) & 1);
          if (KVAT == 1 && sg > 1) mbar_wait(sb + B_MLD + 16, sg & 1);
          if (KVAT == 2 && sg > 1) mbar_wait(sb + B_MLD + 8, (sg - 1) & 1);
          asm volatile("fence.proxy.async.global;" ::: "memory");
          if (elect_one()) { mbar_arrive_tx(sb + B_XFULL, 16384); bulk_load(sb + OFF_KX, kv, 16384, sb + B_XFULL); }
        }
        if (sg == 1 && elect_one()) {
#pragma unroll 1
          for (int i = 0; i < 11; i++) tma_load_2d(sb + OFF_WO + i * 8192, &tmWo, i < 8 ? (i >> 2) * 384 + r * 128 + (i & 3) * 32 : 768 + r * 80 + (i - 8) * 32, h * 128, sb + B_WO);
        }
        if (sg + 4 < 64 && elect_one()) tma_prefetch_2d(&tmX, (cta & 15) * 64, (sg + 4) * 32);
        if (sg < 63) {
          mbar_wait(sb + B_SSE, sg & 1);
#pragma unroll 1
          for (int j = 0; j < 8; j++) load_slot(sg * 32 + 32, j * 64, j);
        }
        mbar_wait(sb + B_XRDY, sg & 1);
        TDUMP(0x1d3ffd00u, sg - 2);
        if (elect_one()) {
          asm volatile("fence.acq_rel.gpu;" ::: "memory");
          if (r > 0 && sg < 63) { mbar_arrive(sb + B_XAV); mbar_arrive_remote(p1 + B_XAV); mbar_arrive_remote(p2 + B_XAV); }
          if (sg > 0) asm volatile("red.relaxed.gpu.global.add.u32 [%0], 1;" :: "l"(g_rflag + sg - 1) : "memory");
        }
      }
      mbar_wait(sb + B_XRDY, 0);
      if (elect_one()) asm volatile("fence.acq_rel.gpu; red.relaxed.gpu.global.add.u32 [%0], 1;" :: "l"(g_rflag + 63) : "memory");
    } else {
      asm volatile("barrier.cluster.wait.aligned;" ::: "memory");
      if (warp == 11) fetcher_warp(sb, cta, &tmP, prm);
      else {
        const int h = cluster_id(), r = cluster_rank();
        mbar_wait(sb + B_WSS, 0);
#pragma unroll 1
        for (int i = (r * 2 + warp - 9) * 32 + lane; i < 2048; i += 192) asm volatile("prefetch.global.L2 [%0];" :: "l"(wo_ptr + (size_t)h * 131072 + i * 64));
        reducer_warp(sb, cta, warp - 9, &tmP);
      }
    }
  } else {
    asm volatile("setmaxnreg.inc.sync.aligned.u32 240;");
    [[maybe_unused]] const int TW = 3;
    const int wg = warp >> 2, wq = warp & 3;
    const int h = cluster_id(), r = cluster_rank();
    {
      uint32_t* gp = g_part + ((8 * r + warp) * 32 + h) * 64 + lane;
#pragma unroll
      for (int rho = 0; rho < 3; rho++) { stg32_relaxed(gp + rho * 24 * 2048, 0u); stg32_relaxed(gp + rho * 24 * 2048 + 32, 0u); }
    }
    if (tid < 192) {
      uint2 m[8];
#pragma unroll
      for (int n = 0; n < 8; n++) m[n] = *(const uint2*)(mem0 + n * 1024 + tid * 4);
      uint32_t dst = sb + OFF_MEM + tid * 64;
      sts128(dst,      __byte_perm(m[0].x, m[1].x, 0x5410), __byte_perm(m[2].x, m[3].x, 0x5410), __byte_perm(m[4].x, m[5].x, 0x5410), __byte_perm(m[6].x, m[7].x, 0x5410));
      sts128(dst + 16, __byte_perm(m[0].x, m[1].x, 0x7632), __byte_perm(m[2].x, m[3].x, 0x7632), __byte_perm(m[4].x, m[5].x, 0x7632), __byte_perm(m[6].x, m[7].x, 0x7632));
      sts128(dst + 32, __byte_perm(m[0].y, m[1].y, 0x5410), __byte_perm(m[2].y, m[3].y, 0x5410), __byte_perm(m[4].y, m[5].y, 0x5410), __byte_perm(m[6].y, m[7].y, 0x5410));
      sts128(dst + 48, __byte_perm(m[0].y, m[1].y, 0x7632), __byte_perm(m[2].y, m[3].y, 0x7632), __byte_perm(m[4].y, m[5].y, 0x7632), __byte_perm(m[6].y, m[7].y, 0x7632));
    }
    {
      const int n = tid >> 5, ch = lane;
      const uint4 m = *(const uint4*)(mem0 + n * 1024 + 768 + ch * 8);
      sts128(sb + ring_off(4) + 4096 + (ch >> 3) * 5120 + n * 128 + (((ch & 7) ^ n) << 4), m.x, m.y, m.z, m.w);
      fence_proxy_async();
    }
    uint32_t a[NRF][4];
    float x0[20];
    {
      const int row = (lane & 7) + ((lane >> 4) << 3), ch = 2 * wq + ((lane >> 3) & 1);
      const uint32_t la = sb + OFF_WO + wg * 8192 + row * 128 + ((ch ^ (row & 7)) << 4);
#pragma unroll
      for (int i = 0; i < 20; i++) x0[i] = 0.f;
#pragma unroll
      for (int c = 0; c < NRF / 4; c++) {
        mbar_wait(sb + B_WFULL + (c % 5) * 8, (c / 5) & 1);
#pragma unroll
        for (int i = 0; i < 4; i++) ldsm4t(a[c * 4 + i], la + (c % 5) * 16384 + i * 2048);
        mbar_wait(sb + B_FULL + (c & 7) * 8, c >> 3);
        WG_FENCE();
#pragma unroll
        for (int i = 0; i < 4; i++) wg_rs32<1>(x0, a[c * 4 + i], mkdesc(SB0 + ring_off(c & 7) + i * 32, 16, 1024, 1));
        WG_COMMIT();
        if (lane == 0) mbar_arrive(sb + B_WEMPTY + (c % 5) * 8);
        WG_WAIT(0);
        if (c < 8 && lane == 0 && wq == 0) mbar_arrive(sb + B_EMPTY + c * 8);
      }
    }
    BAR_SYNC(1, 256);
    asm volatile("barrier.cluster.wait.aligned;" ::: "memory");

    const uint32_t p1 = mapa(sb, r == 2 ? 0 : r + 1), p2 = mapa(sb, r == 0 ? 2 : r - 1);
    const uint64_t wdesc = mkdesc(SB0 + OFF_W + wg * NSS * 2048, 0, 1024, 1);
    const uint32_t l16 = __shfl_sync(0xffffffffu, lane * 16, lane);
    const bool l0 = l16 == 0;

    auto ss_pass = [&](float* acc) {
#pragma unroll
      for (int i = 0; i < NSS; i++) {
        if (i % 4 == 0) { if (i > 0) mbar_spin(sb + B_FULL + (4 + i / 4) * 8, 1); WG_FENCE(); }
        wg_ss40(acc, wdesc + i * 128, mkdesc(SB0 + ring_off(4 + i / 4) + (i & 3) * 32, 16, 1024, 1));
      }
      WG_COMMIT();
    };
    {
      mbar_spin(sb + B_FULL + 4 * 8, 1);
      mbar_spin(sb + B_WSS, 0);
      ss_pass(x0);
      WG_WAIT(0);
      mbar_arrive_if(l0 && wq == 0, sb + B_SSE);
      uint4* gi = (uint4*)((uint8_t*)g_img + (uint32_t)((h * 3 + r) * 8192 + warp * 1024 + ((lane ^ ((lane >> 3) & 3)) << 4)));
      gi[0] = make_uint4(pack_bf16(x0[0], x0[1]), pack_bf16(x0[4], x0[5]), pack_bf16(x0[8], x0[9]), pack_bf16(x0[12], x0[13]));
      gi[32] = make_uint4(pack_bf16(x0[2], x0[3]), pack_bf16(x0[6], x0[7]), pack_bf16(x0[10], x0[11]), pack_bf16(x0[14], x0[15]));
      __syncwarp();
      mbar_arrive_if(l0, sb + B_XRDY);
    }
    uint32_t okx = 0;
#pragma unroll 1
    for (int s = 0;; s++) {
      const uint32_t par = s & 1;
      float xa[20];
#pragma unroll
      for (int j = 16; j < 20; j++) xa[j] = 0.f;
      if (LIKELY(s < 63)) {
#pragma unroll
        for (int c = 0; c < NRF / 4; c++) {
          if (UNLIKELY(!okx)) mbar_spin(sb + B_FULL + (c & 7) * 8, c >> 3);
          okx = mbar_test(sb + B_FULL + ((c + 1) & 7) * 8, (c + 1) >> 3);
          WG_FENCE();
#pragma unroll
          for (int i = 0; i < 4; i++) {
            const uint64_t bd = mkdesc(SB0 + ring_off(c & 7) + i * 32, 16, 1024, 1);
            if (c + i == 0) wg_rs32<0>(xa, a[0], bd); else wg_rs32<1>(xa, a[c * 4 + i], bd);
          }
          WG_COMMIT();
          if (c == 8) TSTAMP(26);
          if (c > 0) { WG_WAIT(1); if (c <= 8) mbar_arrive_if(l0 && wq == 0, sb + B_EMPTY + (c - 1) * 8); }
        }
        TSTAMP(0);
        if (UNLIKELY(!okx)) mbar_spin(sb + B_FULL + 4 * 8, 1);
        mbar_spin(sb + B_MEM + 16, par);
        WG_WAIT(0);
      } else {
#pragma unroll
        for (int i = 0; i < 16; i++) xa[i] = 0.f;
        mbar_spin(sb + B_MEM + 16, par);
      }
      TSTAMP(1);
      ss_pass(xa);
      mbar_spin(sb + B_MLD, par);
      const uint32_t mb = sb + OFF_MEM + l16;
      uint32_t b[3][4];
      ldsm4t(b[0], mb); ldsm4t(b[1], mb + 512);
      WG_WAIT(0);
      TSTAMP(2);
      uint32_t xl[4], xh[4];
#pragma unroll
      for (int n = 0; n < 4; n++) { xl[n] = pack_bf16(xa[4 * n], xa[4 * n + 1]); xh[n] = pack_bf16(xa[4 * n + 2], xa[4 * n + 3]); }
      auto put_x = [&]() {
        uint4* gi = (uint4*)((uint8_t*)g_img + (uint32_t)((((s + 1) * 32 + h) * 3 + r) * 8192 + warp * 1024 + (l16 ^ ((l16 >> 3) & 0x30))));
        gi[0] = make_uint4(xl[0], xl[1], xl[2], xl[3]);
        gi[32] = make_uint4(xh[0], xh[1], xh[2], xh[3]);
        __syncwarp();
      };
      {
        float v[4], d[G1CH][4];
        uint32_t ok1 = 0;
#pragma unroll
        for (int i = 0; i < NRF / 2; i++) {
          if (i == 7) ok1 = mbar_test(sb + B_MLD + 8, par) & mbar_test(sb + B_XFULL, par) & (s != 0);
          if (i == 10) {
            if (UNLIKELY(!ok1)) { mbar_spin(sb + B_MLD + 8, par); if (s < 63) mbar_spin(sb + B_XFULL, par); mbar_spin(sb + B_WO, 0); }
            mbar_arrive_if(l0 && wq == 0, sb + B_REF);
          }
          if (i == SSEAT) mbar_arrive_if(l0 && wq == 0, sb + B_SSE);
          if (i + 2 < NRF / 2) ldsm4t(b[(i + 2) % 3], mb + (i + 2) * 512);
          if (i == NRF / 2 - 3) { ok1 = mbar_test(sb + B_MEM, par); __syncwarp(); ok1 &= lds32(sb + OFF_LATE) != s; }
#pragma unroll
          for (int j = 0; j < 2; j++) {
            const int kk = 2 * i + j;
            if (kk < G1CH) mma16816z(d[kk], a[kk], b[i % 3][2 * j], b[i % 3][2 * j + 1]);
            else mma16816v(d[kk % G1CH], a[kk], b[i % 3][2 * j], b[i % 3][2 * j + 1]);
          }
        }
        uint32_t qoff = OFF_QM + r * 2048 + warp * 256 + (l16 >> 2), ra1 = p1 + qoff, ra2 = p2 + qoff;
        if (PINQ) { PIN(qoff); PIN(ra1); PIN(ra2); }
        TSTAMP(29);
        if (UNLIKELY(!ok1)) {
          mbar_spin(sb + B_MEM, par);
          if (lds32(sb + OFF_LATE) == s) {
#pragma unroll
            for (int j = 0; j < 4 * G1CH; j++) d[j >> 2][j & 3] = 0.f;
#pragma unroll
            for (int i = 0; i < NRF / 2; i++) {
              ldsm4t(b[0], mb + i * 512);
              mma16816v(d[0], a[2 * i], b[0][0], b[0][1]); mma16816v(d[1], a[2 * i + 1], b[0][2], b[0][3]);
            }
          }
        }
#pragma unroll
        for (int j = 0; j < 4; j++) v[j] = G1CH == 2 ? (d[0][j] + xa[16 + j]) + d[1][j] : (d[0][j] + xa[16 + j]) + (d[1][j] + d[G1CH - 1][j]);
        const uint32_t w0 = pack_bf16(v[0], v[1]), w1 = pack_bf16(v[2], v[3]);
        st_async32(ra1, w0, p1 + B_QKV); st_async32(ra1 + 128, w1, p1 + B_QKV);
        st_async32(ra2, w0, p2 + B_QKV); st_async32(ra2 + 128, w1, p2 + B_QKV);
        sts32(sb + qoff, w0); sts32(sb + qoff + 128, w1);
        __syncwarp();
        mbar_arrive_tx_if(l0, sb + B_QKV, 512);
        if (SSEAT > 23) mbar_arrive_if(l0 && wq == 0, sb + B_SSE);
        TSTAMP(3);
      }
      auto put_kv_mem = [&]() {
        mbar_spin(sb + B_QKV, par);
        if (r > 0) {
          uint4* gm = (uint4*)((uint8_t*)g_imgm + ((s * 32 + h) * 2 + r - 1) * 2048 + l16);
#pragma unroll
          for (int j = 0; j < 4; j++) { uint32_t w[4]; lds128(w, sb + OFF_QM + r * 2048 + j * 512 + l16); gm[j * 32] = make_uint4(w[0], w[1], w[2], w[3]); }
        }
      };
      if (UNLIKELY(s == 63)) { if (warp == 7) { put_kv_mem(); __syncwarp(); } mbar_arrive_if(l0, sb + B_XRDY); break; }
      TSTAMP(9);
      uint32_t la = sb + OFF_WO + (warp >> 1) * 8192 + (l16 & 0x70) * 4 + (l16 & 0x100) * 2 + ((((warp & 1) << 5) + ((l16 >> 3) & 0x10)) ^ ((l16 >> 1) & 0x30));
      la = __shfl_sync(0xffffffffu, la, l16 >> 4);
      constexpr int LA = 4;
      uint32_t wr[LA][4];
      const bool first = warp >= (r == 0 ? 2 : 3);
      constexpr uint32_t O2 = 65536 - 8192;
      auto wo_first = [&]() {
#pragma unroll
        for (int n = 0; n < LA; n++) ldsm4t(wr[n], la + (first ? O2 : 0) + n * 1024);
      };
      auto scores = [&](const uint32_t (&k)[4][4], uint32_t qa) {
        uint32_t q[4][4];
        float x0[4], x1[4], y0[4], y1[4];
        ldsm4t(q[0], qa); ldsm4t(q[1], qa + 256); ldsm4t(q[2], qa + 512);
        mma16816z(x0, q[0], k[0][0], k[0][1]); mma16816z(y0, q[0], k[2][0], k[2][1]);
        ldsm4t(q[3], qa + 768);
        mma16816z(x1, q[1], k[0][2], k[0][3]); mma16816z(y1, q[1], k[2][2], k[2][3]);
        mma16816v(x0, q[2], k[1][0], k[1][1]); mma16816v(y0, q[2], k[3][0], k[3][1]);
        mma16816v(x1, q[3], k[1][2], k[1][3]); mma16816v(y1, q[3], k[3][2], k[3][3]);
        sts64(sb + OFF_S + warp * 256 + (l16 >> 1), __float_as_uint((x0[0] + y0[2]) + (x1[0] + y1[2])), __float_as_uint((x0[1] + y0[3]) + (x1[1] + y1[3])));
      };
      if (LIKELY(warp < 4)) {
        {
          uint32_t qa = sb + OFF_QM + (l16 & 0x70) + ((l16 & 0x80) << 3) + ((l16 & 0x100) >> 1);
          uint32_t k[4][4];
          const uint32_t kb = sb + OFF_KX + l16 * 4 + (((warp << 4) ^ (l16 >> 1)) & 0x30);
#pragma unroll
          for (int j = 0; j < 4; j++) ldsm4t(k[j], kb + j * 2048);
          __syncwarp();
          put_x();
          mbar_arrive_if(l0, sb + B_XRDY);
          PIN(qa);
          mbar_spin(sb + B_QKV, par);
          TSTAMP(4);
          scores(k, qa);
          TSTAMP(22);
        }
        uint32_t va = sb + OFF_VX + warp * 2048 + (l16 & 0xf0) * 4 + (((l16 >> 4) ^ (l16 >> 1)) & 0x10) + ((l16 >> 1) & 0x20);
        PIN(va);
        BAR_SYNC(2, 192);
        float sc[12];
#pragma unroll
        for (int j = 5; j >= 0; j--) lds64f(sc[2 * j], sc[2 * j + 1], sb + OFF_S + j * 256 + (l16 >> 1));
        sc[8] += sc[10]; sc[9] += sc[11];
        uint32_t v0[4], v1[4], v2[4], v3[4], vm[4];
        ldsm4(v0, va); ldsm4(v2, va + 1024); ldsm4(v1, va ^ 0x20); ldsm4(v3, (va ^ 0x20) + 1024);
        float mx = fmaxf(fmaxf(fmaxf(sc[0], sc[1]), fmaxf(sc[2], sc[3])), fmaxf(fmaxf(sc[4], sc[5]), fmaxf(sc[6], sc[7])));
        mx = fmaxf(mx, fmaxf(sc[8], sc[9]));
        mx = fmaxf(fmaxf(mx, __shfl_xor_sync(0xffffffffu, mx, 1)), fmaxf(__shfl_xor_sync(0xffffffffu, mx, 2), __shfl_xor_sync(0xffffffffu, mx, 3)));
        const float cs = 0.08838834764831845f * 1.4426950408889634f;
        const float nm = -mx * cs;
        uint32_t p[5];
        const uint32_t ones[4] = {0x3f803f80u, 0x3f803f80u, 0x3f803f80u, 0x3f803f80u};
        float o0[4], o1[4], z[4];
#pragma unroll
        for (int j = 0; j < 5; j++) {
          p[j] = pack_bf16(ex2f(fmaf(sc[2 * j], cs, nm)), ex2f(fmaf(sc[2 * j + 1], cs, nm)));
          if (j == 1) { mma16816z(z, ones, p[0], p[1]); mma16816z(o0, v0, p[0], p[1]); mma16816z(o1, v2, p[0], p[1]); ldsm4(vm, sb + OFF_QM + 4096 + warp * 512 + l16); }
          if (j == 3) { mma16816v(z, ones, p[2], p[3]); mma16816v(o0, v1, p[2], p[3]); mma16816v(o1, v3, p[2], p[3]); }
        }
        mma1688(z, ones[0], ones[1], p[4]); mma1688(o0, vm[0], vm[1], p[4]); mma1688(o1, vm[2], vm[3], p[4]);
        wo_first();
        __syncwarp();
        const float i0 = rcpf(z[0]), i1 = rcpf(z[1]);
        const uint32_t oa = sb + OFF_O + warp * 512 + (l16 >> 2);
        sts32(oa, pack_bf16(o0[0] * i0, o0[1] * i1)); sts32(oa + 128, pack_bf16(o0[2] * i0, o0[3] * i1));
        sts32(oa + 256, pack_bf16(o1[0] * i0, o1[1] * i1)); sts32(oa + 384, pack_bf16(o1[2] * i0, o1[3] * i1));
        __syncwarp();
        mbar_arrive_if(l0, sb + B_OF);
        TSTAMP(23);
      } else if (warp == 5 || warp == 6) {
        put_x();
        mbar_arrive_if(l0, sb + B_XRDY);
        uint32_t qa = sb + OFF_QM + (warp - 5) * 1024 + (l16 & 0x70) + ((l16 & 0x80) << 2) + ((l16 & 0x100) >> 1);
        uint32_t ka = sb + OFF_QM + 2048 + (warp - 5) * 1024 + l16;
        PIN(qa); PIN(ka);
        mbar_spin(sb + B_QKV, par);
        uint32_t q0[4], q1[4], k0[4], k1[4];
        float x0[4], x1[4], y0[4], y1[4];
        ldsm4t(q0, qa); ldsm4t(k0, ka); ldsm4t(k1, ka + 512); ldsm4t(q1, qa + 256);
        mma16816z(x0, q0, k0[0], k0[1]); mma16816z(y0, q0, k1[0], k1[1]);
        mma16816z(x1, q1, k0[2], k0[3]); mma16816z(y1, q1, k1[2], k1[3]);
        sts64(sb + OFF_S + (warp - 1) * 256 + (l16 >> 1), __float_as_uint((x0[0] + y0[2]) + (x1[0] + y1[2])), __float_as_uint((x0[1] + y0[3]) + (x1[1] + y1[3])));
        asm volatile("bar.arrive 2, 192;" ::: "memory");
        wo_first();
      } else {
        put_x();
        if (warp == 7) put_kv_mem();
        __syncwarp();
        mbar_arrive_if(l0, sb + B_XRDY);
        wo_first();
      }
      {
        mbar_spin(sb + (HOLD && !first ? (HOLD == 1 ? B_SIG + 16 : B_GO) : B_OF), par);
        uint32_t ob[16];
#pragma unroll
        for (int j = 0; j < 4; j++) ldsm4t(ob + 4 * j, sb + OFF_O + j * 512 + l16);
        TSTAMP(5);
        const uint32_t rc = par << 16, tag = par ^ 1;
        uint32_t* const gp = (uint32_t*)((uint8_t*)(g_part + ((8 * r + warp) * 32 + h) * 64) + ((l16 + par) >> 2));
        float c[4], e[4];
        static_assert(8 % LA == 0, "");
        if (first) {
#pragma unroll
          for (int kk = 0; kk < 8; kk++) {
            float* acc = (kk & 1) ? e : c;
            if (kk < 2) mma16816z(acc, wr[kk % LA], ob[2 * kk], ob[2 * kk + 1]); else mma16816v(acc, wr[kk % LA], ob[2 * kk], ob[2 * kk + 1]);
            if (kk + LA < 8) ldsm4t(wr[kk % LA], la + O2 + (kk + LA) * 1024);
            if (HOLD >= 2 && kk == HOLD - 2) mbar_arrive_if(l0 && warp == 3, sb + B_GO);
            if (EARLYLA && kk >= 8 - EARLYLA) ldsm4t(wr[kk - (8 - EARLYLA)], la + (kk - (8 - EARLYLA)) * 1024);
          }
#pragma unroll
          for (int j = 0; j < 4; j++) c[j] += e[j];
          if ((l16 & 0xc0) == 0) { c[0] = tag_round(c[0], rc); c[1] = tag_round(c[1], rc); }
          uint32_t x = movmat(pack_bf16(c[0], c[1]));
          const uint32_t y = movmat(pack_bf16(c[2], c[3]));
          if ((l16 & 0x10) == 0) x = (x & ~1u) | tag;
          stg64_relaxed(gp + 48 * 2048 + (l16 >> 4), x, y);
          mbar_arrive_if(l0, sb + B_SIG + 16);
          TSTAMP(30); TSTAMPW(31, 4);
#pragma unroll
          for (int n = EARLYLA; n < LA; n++) ldsm4t(wr[n], la + n * 1024);
        }
        const bool t0 = (l16 & 0x30) == 0;
#pragma unroll
        for (int n = 0; n < 16; n++) {
          const int rho = n >> 3, kk = n & 7;
          float* acc = (kk & 1) ? e : c;
          if (kk < 2) mma16816z(acc, wr[n % LA], ob[2 * kk], ob[2 * kk + 1]); else mma16816v(acc, wr[n % LA], ob[2 * kk], ob[2 * kk + 1]);
          if (n + LA < 16) ldsm4t(wr[n % LA], la + ((n + LA) >> 3) * 32768 + ((n + LA) & 7) * 1024);
          if (n == 12) okx = mbar_test(sb + B_FULL, 0);
          if (kk == 7) {
#pragma unroll
            for (int j = 0; j < 4; j++) c[j] += e[j];
            if (t0) { c[0] = tag_round(c[0], rc); c[2] = tag_round(c[2], rc); }
            uint32_t x = pack_bf16(c[0], c[1]), y = pack_bf16(c[2], c[3]);
            if (t0) { x = (x & ~1u) | tag; y = (y & ~1u) | tag; }
            stg32_relaxed(gp + rho * 24 * 2048, x);
            stg32_relaxed(gp + rho * 24 * 2048 + 32, y);
            mbar_arrive_if(l0, sb + B_SIG + rho * 8);
            if (rho == 0) TSTAMP(6);
          }
        }
      }
      if (PHBAR & 1) BAR_SYNC(1, 256);
      TSTAMP(7);
    }
  }
  asm volatile("barrier.cluster.arrive.release.aligned; barrier.cluster.wait.acquire.aligned;" ::: "memory");
}

namespace gk {
constexpr uint32_t SB0 = 1024;
constexpr uint32_t STAGE = 49152, OFF_STG = 4 * STAGE, OFF_BAR = OFF_STG + 32768;
constexpr uint32_t B_FULL = OFF_BAR, B_EMPTY = B_FULL + 32, B_IFULL = B_EMPTY + 32, B_IEMPTY = B_IFULL + 16, B_SFULL = B_IEMPTY + 16, B_SEMPTY = B_SFULL + 16, OFF_ITEM = B_SEMPTY + 16;
constexpr uint32_t SMEM_BYTES = OFF_ITEM + 16;
constexpr int N_QKV = 192, N_ATA = 128, N_OUTA = 64;
constexpr int I_ATA = N_QKV, I_OUTA = I_ATA + N_ATA, I_B = I_OUTA + N_OUTA;
#define RELAT 12
#define WSLEEP 250
#define NWIDE 13
#define SEGF 48
constexpr int NW = NWIDE;
constexpr int I_BM = I_B + NW * 4, I_BN = I_BM + (14 - NW) * 8, I_BS = I_BN + 16, I_ATB = I_BS + 64;
constexpr int SF = SEGF, N_ATB = 2 * SF + 8 * (64 - SF), N_ITEMS = I_ATB + N_ATB;
enum { T_QKV, T_ATA, T_OUTA, T_ATB, T_OUTB, T_OUTBM, T_OUTBN, T_OUTBS, T_DONE };
constexpr int C_NEXT = 0, C_NEXTB = 32, C_EXIT = 64, C_CLM = 96, C_QKV = 160, C_ATA = C_QKV + 128, C_ATB = C_ATA + 128, N_CNT = C_ATB + 256;
}
__device__ __align__(256) __nv_bfloat16 g_qkvA[2048 * 3072];
__device__ __align__(256) __nv_bfloat16 g_oA[2048 * 1024];
__device__ __align__(256) __nv_bfloat16 g_oB[2048 * 4096];
__device__ __align__(256) uint32_t g_cnt[gk::N_CNT];

struct GMaps { CUtensorMap xA, wqkv, qkvSt, qkvQ, qkvKV, oA, wo, oB, Wo, oBs, Wos, out; __nv_bfloat16* outp; };

DEVI void decode_item(int idx, int& type, int& m, int& n) {
  using namespace gk;
  if (idx < I_ATA) { type = T_QKV; m = idx / 12; n = idx - m * 12; }
  else if (idx < I_OUTA) { type = T_ATA; m = (idx - I_ATA) >> 2; n = idx & 3; }
  else if (idx < I_B) { type = T_OUTA; m = (idx - I_OUTA) >> 2; n = idx & 3; }
  else if (idx < I_BM) { type = T_OUTB; m = (idx - I_B) >> 2; n = idx & 3; }
  else if (idx < I_BN) { type = T_OUTBM; m = NW + ((idx - I_BM) >> 3); n = (idx - I_BM) & 7; }
  else if (idx < I_BS) { type = T_OUTBN; m = 14; n = idx - I_BN; }
  else if (idx < I_ATB) { type = T_OUTBS; m = 30 + ((idx - I_BS) >> 5); n = (idx - I_BS) & 31; }
  else if (idx < N_ITEMS) {
    const int i = idx - I_ATB;
    type = T_ATB;
    if (i < 2 * SF) { m = i >> 1; n = (i & 1) * 16; } else { m = SF + ((i - 2 * SF) >> 3); n = (i & 7) * 4; }
  }
  else { type = T_DONE; m = n = 0; }
}
DEVI void wait_count(const uint32_t* p, uint32_t target) {
  for (int it = 0;; it++) {
    uint32_t v; asm volatile("ld.acquire.gpu.global.u32 %0, [%1];" : "=r"(v) : "l"(p) : "memory");
    if (v >= target) break;
    if (it > 4000000) asm volatile("trap;");
    __nanosleep(WSLEEP);
  }
}
DEVI int next_item(int& held) {
  using namespace gk;
  auto need = [](int j) -> uint32_t {
    const int sg = j < I_B ? 0 : (j < I_BM ? 4 * (((j - I_B) >> 2) + 1) : (j < I_BN ? 4 * (NW + ((j - I_BM) >> 3) + 1) : (j < I_BS ? 60 : 64)));
    return sg <= SF ? 2 * sg : 2 * SF + 8 * (sg - SF);
  };
  for (int it = 0;; it++) {
    const uint32_t i = ldg32_relaxed(g_cnt + C_NEXTB);
    if (i < N_ATB && (held < 0 || i < need(held))) {
      const uint32_t sg = i < 2 * SF ? i >> 1 : SF + ((i - 2 * SF) >> 3);
      const uint32_t f = ldg32_relaxed(g_rflag + sg), fp = ldg32_relaxed(g_rflag + max((int)sg - 1, 0));
      if (f >= 96 || (held >= 0 && sg >= SF && fp >= 96)) {
        const uint32_t per = sg < SF ? 2 : 8, k = atomicAdd(&g_cnt[C_CLM + sg], 1);
        if (k == per - 1) atomicAdd(&g_cnt[C_NEXTB], per);
        if (k < per) return I_ATB + i + k;
      }
    }
    if (held < 0) held = min((int)atomicAdd(&g_cnt[C_NEXT], 1), I_ATB);
    if (i >= need(held)) { const int j = held; held = -1; return j < I_ATB ? j : N_ITEMS; }
    if (it > 4000000) asm volatile("trap;");
    __nanosleep(200);
  }
}
DEVI void signal_count(uint32_t* p, uint32_t n = 1) { asm volatile("fence.acq_rel.gpu; red.relaxed.gpu.global.add.u32 [%0], %1;" :: "l"(p), "r"(n) : "memory"); }
DEVI void mbar_arrive_n(uint32_t bar, uint32_t n) { asm volatile("mbarrier.arrive.shared::cta.b64 _, [%0], %1;" :: "r"(bar), "r"(n) : "memory"); }
DEVI void stsm4(uint32_t a, uint32_t r0, uint32_t r1, uint32_t r2, uint32_t r3) {
  asm volatile("stmatrix.sync.aligned.m8n8.x4.shared.b16 [%0], {%1,%2,%3,%4};" :: "r"(a), "r"(r0), "r"(r1), "r"(r2), "r"(r3) : "memory");
}

template <int BN>
DEVI void gemm_tile(const uint32_t sb, const int wg, const int wq, const int lane, uint32_t& it, uint32_t& ev, const int nkb) {
  using namespace gk;
  float acc[BN / 2];
#pragma unroll
  for (int i = 0; i < BN / 2; i++) acc[i] = 0.f;
  for (int kb = 0; kb < nkb; kb++, it++) {
    const uint32_t st = it & 3;
    mbar_wait(sb + B_FULL + st * 8, (it >> 2) & 1);
    const uint64_t ad = mkdesc(SB0, 16, 1024, 1) + (st * (STAGE / 16) + wg * 512), bd = mkdesc(SB0 + 16384, 8192, 1024, 1) + st * (STAGE / 16);
    WG_FENCE();
#pragma unroll
    for (int k = 0; k < 4; k++) {
      if constexpr (BN == 256) wg_ss256_tb(acc, ad + k * 2, bd + k * 128, 1);
      else if constexpr (BN == 128) wg_ss128_tb(acc, ad + k * 2, bd + k * 128, 1);
      else wg_ss64_tb(acc, ad + k * 2, bd + k * 128, 1);
    }
    WG_COMMIT();
    if (kb > 0) { WG_WAIT(1); if (lane == 0) mbar_arrive(sb + B_EMPTY + ((it - 1) & 3) * 8); }
  }
  WG_WAIT(0);
  acc_fence<BN / 2>(acc);
  if (lane == 0) mbar_arrive(sb + B_EMPTY + ((it - 1) & 3) * 8);
  const uint32_t stg = sb + OFF_STG + wg * 16384;
  const int row = wq * 16 + (lane & 15);
  const uint32_t sa = stg + row * 128, sw = (row & 7) ^ (lane >> 4);
#pragma unroll
  for (int p = 0; p < (BN + 127) / 128; p++, ev++) {
    mbar_wait(sb + B_SEMPTY + wg * 8, (ev & 1) ^ 1);
#pragma unroll
    for (int j = 0; j < (BN < 128 ? BN : 128) / 16; j++) {
      const float* a = acc + p * 64 + j * 8;
      stsm4(sa + (j >> 2) * 8192 + ((sw ^ ((j & 3) * 2)) << 4), pack_bf16(a[0], a[1]), pack_bf16(a[2], a[3]), pack_bf16(a[4], a[5]), pack_bf16(a[6], a[7]));
    }
    fence_proxy_async();
    __syncwarp();
    if (lane == 0) mbar_arrive(sb + B_SFULL + wg * 8);
  }
}

DEVI void gemm_small(const uint32_t sb, const int wg, const int wq, const int lane, uint32_t& it, uint32_t& ev, __nv_bfloat16* dst) {
  using namespace gk;
  float acc[16];
#pragma unroll
  for (int i = 0; i < 16; i++) acc[i] = 0.f;
  for (int kb = 0; kb < 16; kb++, it++) {
    const uint32_t st = it & 3;
    mbar_wait(sb + B_FULL + st * 8, (it >> 2) & 1);
    const uint64_t ad = mkdesc(SB0, 16, 1024, 1) + (st * (STAGE / 16) + wg * 1024), bd = mkdesc(SB0 + 32768, 16, 512, 2) + (st * (STAGE / 16) + wg * 512);
    WG_FENCE();
#pragma unroll
    for (int k = 0; k < 8; k++) wg_ss32_tb(acc, ad + ((k >> 2) * 512 + (k & 3) * 2), bd + k * 64, 1);
    WG_COMMIT();
    WG_WAIT(0);
    if (lane == 0) mbar_arrive(sb + B_EMPTY + st * 8);
  }
  acc_fence<16>(acc);
  mbar_wait(sb + B_SEMPTY + wg * 8, (ev & 1) ^ 1); ev++;
  const uint32_t mine = sb + OFF_STG + wg * 16384 + (wq * 32 + lane) * 16, other = mine ^ 16384;
  const float* give = acc + 8;
  float keep[8];
#pragma unroll
  for (int i = 0; i < 8; i++) { keep[i] = wg ? acc[8 + i] : acc[i]; acc[8 + i] = wg ? acc[i] : acc[8 + i]; }
  sts128(mine, __float_as_uint(give[0]), __float_as_uint(give[1]), __float_as_uint(give[2]), __float_as_uint(give[3]));
  sts128(mine + 2048, __float_as_uint(give[4]), __float_as_uint(give[5]), __float_as_uint(give[6]), __float_as_uint(give[7]));
  BAR_SYNC(4, 256);
  uint32_t w[8];
  lds128(w, other); lds128(w + 4, other + 2048);
  uint32_t* p = (uint32_t*)(dst + (size_t)(wq * 16 + (lane >> 2)) * 2048 + wg * 16 + (lane & 3) * 2);
#pragma unroll
  for (int j = 0; j < 2; j++) {
    p[j * 4] = pack_bf16(keep[4 * j] + __uint_as_float(w[4 * j]), keep[4 * j + 1] + __uint_as_float(w[4 * j + 1]));
    p[j * 4 + 8192] = pack_bf16(keep[4 * j + 2] + __uint_as_float(w[4 * j + 2]), keep[4 * j + 3] + __uint_as_float(w[4 * j + 3]));
  }
  BAR_SYNC(4, 256);
  if (lane == 0) mbar_arrive(sb + B_SFULL + wg * 8);
}

DEVI void attn_a_unit(const uint32_t sb, const uint32_t st, const int wg, const int wq, const int lane, const int qb, const int head, const bool last) {
  using namespace gk;
  const uint64_t dq = mkdesc(SB0, 16, 512, 2) + st * (STAGE / 16);
  float s[160];
#pragma unroll
  for (int i = 0; i < 160; i++) s[i] = 0.f;
  WG_FENCE();
#pragma unroll
  for (int hf = 0; hf < 2; hf++)
#pragma unroll
    for (int k = 0; k < 2; k++) wg_ss160(s + hf * 80, dq + k * 2, dq + (256 + hf * 640 + k * 2), k);
  WG_COMMIT();
  WG_WAIT(0);
  acc_fence<160>(s);
  const int g = lane >> 2, t2 = (lane & 3) * 2;
  const float NEG = -INFINITY;
  if (qb < 4) {
#pragma unroll
    for (int c = 0; c < 4; c++)
      if (c < 4 - qb)
#pragma unroll
        for (int i = 0; i < 32; i++) s[c * 32 + i] = NEG;
  }
  const bool k0 = t2 > g, k1 = t2 + 1 > g;
  auto diag = [&](float* lo, float* hi) {
    if (!k0) { lo[0] = NEG; lo[6] = NEG; } else { hi[0] = NEG; hi[6] = NEG; }
    if (!k1) { lo[1] = NEG; lo[7] = NEG; } else { hi[1] = NEG; hi[7] = NEG; }
    lo[2] = NEG; lo[3] = NEG; hi[4] = NEG; hi[5] = NEG;
  };
  int u0 = 0x80000000, u1 = 0x80000000, u2 = 0x80000000, u3 = 0x80000000;
  auto imax = [&](const float* a) {
    u0 = __vimax3_s32(u0, __float_as_int(a[0]), __float_as_int(a[1])); u1 = __vimax3_s32(u1, __float_as_int(a[2]), __float_as_int(a[3]));
    u2 = __vimax3_s32(u2, __float_as_int(a[4]), __float_as_int(a[5])); u3 = __vimax3_s32(u3, __float_as_int(a[6]), __float_as_int(a[7]));
  };
#pragma unroll
  for (int y = 0; y < 4; y++) {
    if (y == wq) diag(s + y * 8, s + (y + 16) * 8);
    if (y >= wq) imax(s + y * 8);
    if (y <= wq) imax(s + (y + 16) * 8);
  }
#pragma unroll
  for (int y = 4; y < 16; y++) imax(s + y * 8);
  u0 = max(u0, u2); u1 = max(u1, u3);
  u0 = max(__vimax3_s32(u0, __shfl_xor_sync(0xffffffffu, u0, 1), __shfl_xor_sync(0xffffffffu, u0, 2)), __shfl_xor_sync(0xffffffffu, u0, 3));
  u1 = max(__vimax3_s32(u1, __shfl_xor_sync(0xffffffffu, u1, 1), __shfl_xor_sync(0xffffffffu, u1, 2)), __shfl_xor_sync(0xffffffffu, u1, 3));
  float m0 = __int_as_float(u0), m1 = __int_as_float(u1);
  if (__any_sync(0xffffffffu, (u0 | u1) < 0)) {
    m0 = NEG; m1 = NEG;
#pragma unroll
    for (int y = 0; y < 20; y++) {
      const float* a = s + y * 8;
      if (y >= wq && y <= wq + 16) {
        m0 = fmaxf(m0, fmaxf(fmaxf(a[0], a[1]), fmaxf(a[4], a[5])));
        m1 = fmaxf(m1, fmaxf(fmaxf(a[2], a[3]), fmaxf(a[6], a[7])));
      }
    }
    m0 = fmaxf(m0, __shfl_xor_sync(0xffffffffu, m0, 1)); m1 = fmaxf(m1, __shfl_xor_sync(0xffffffffu, m1, 1));
    m0 = fmaxf(m0, __shfl_xor_sync(0xffffffffu, m0, 2)); m1 = fmaxf(m1, __shfl_xor_sync(0xffffffffu, m1, 2));
  }
  const float cs = 0.17677669529663687f * 1.4426950408889634f;
  const float n0 = -m0 * cs, n1 = -m1 * cs;
  float l0 = 0.f, l1 = 0.f;
  uint32_t p[80];
  if (RELAT >= 0) { if (wg == 0) BAR_SYNC(1, 256); else BAR_SYNC(2, 256); }
#pragma unroll
  for (int y = 0; y < 20; y++) {
    const float* a = s + y * 8;
    if ((y >= 3 || y >= wq) && (y <= 16 || y <= wq + 16)) {
      float e[8];
#pragma unroll
      for (int i = 0; i < 8; i++) e[i] = ex2f(fmaf(a[i], cs, (i & 2) ? n1 : n0));
      l0 += (e[0] + e[1]) + (e[4] + e[5]); l1 += (e[2] + e[3]) + (e[6] + e[7]);
#pragma unroll
      for (int i = 0; i < 4; i++) p[y * 4 + i] = pack_bf16(e[2 * i], e[2 * i + 1]);
    } else {
#pragma unroll
      for (int i = 0; i < 4; i++) p[y * 4 + i] = 0;
    }
    if (y == RELAT) { if (wg == 0) asm volatile("bar.arrive 2, 256;" ::: "memory"); else if (!last) asm volatile("bar.arrive 1, 256;" ::: "memory"); }
  }
  float o[16];
#pragma unroll
  for (int i = 0; i < 16; i++) o[i] = 0.f;
  WG_FENCE();
#pragma unroll
  for (int y = 0; y < 20; y++) wg_rs32_tb(o, p[y * 4], p[y * 4 + 1], p[y * 4 + 2], p[y * 4 + 3], dq + (1536 + y * 64), y);
  WG_COMMIT();
  l0 += __shfl_xor_sync(0xffffffffu, l0, 1); l1 += __shfl_xor_sync(0xffffffffu, l1, 1);
  l0 += __shfl_xor_sync(0xffffffffu, l0, 2); l1 += __shfl_xor_sync(0xffffffffu, l1, 2);
  const float i0 = rcpf(l0), i1 = rcpf(l1);
  uint4* dst = (uint4*)(g_oA + (size_t)(qb * 64 + wq * 16 + g) * 1024 + head * 32 + t2 * 4);
  const uint32_t stg = sb + OFF_STG + wg * 16384 + wq * 1024;
  WG_WAIT(0);
  acc_fence<16>(o);
  if (lane == 0) mbar_arrive_n(sb + B_EMPTY + st * 8, 2);
#pragma unroll
  for (int j = 0; j < 2; j++)
    stsm4(stg + (lane & 15) * 64 + (((2 * j + (lane >> 4)) ^ ((lane >> 1) & 3)) << 4), pack_bf16(o[j * 8] * i0, o[j * 8 + 1] * i0), pack_bf16(o[j * 8 + 2] * i1, o[j * 8 + 3] * i1),
          pack_bf16(o[j * 8 + 4] * i0, o[j * 8 + 5] * i0), pack_bf16(o[j * 8 + 6] * i1, o[j * 8 + 7] * i1));
  __syncwarp();
  uint32_t w[8];
  const uint32_t ra = stg + g * 64 + (((lane & 3) ^ (g >> 1)) << 4);
  lds128(w, ra); lds128(w + 4, ra + 512);
  dst[0] = make_uint4(w[0], w[1], w[2], w[3]);
  dst[1024] = make_uint4(w[4], w[5], w[6], w[7]);
}

DEVI void attn_b_unit(const uint32_t sb, const uint32_t st, const int warp, const int lane, const int seg, const int head) {
  using namespace gk;
  const uint32_t base = sb + st * STAGE;
  const int mt = warp & 1, g = lane >> 2, t = lane & 3;
  const uint32_t sw = (lane >> 1) & 3;
  float s[5][4];
#pragma unroll
  for (int c = 0; c < 5; c++) { s[c][0] = s[c][1] = s[c][2] = s[c][3] = 0.f; }
  const uint32_t qa = base + ((lane & 7) + ((lane >> 4) << 3)) * 64 + (((2 * mt + ((lane >> 3) & 1)) ^ sw) << 4);
#pragma unroll
  for (int j = 0; j < 4; j++) {
    uint32_t q0[4], q1[4], k[4];
    ldsm4t(q0, qa + j * 2048); ldsm4t(q1, qa + j * 2048 + 1024);
#pragma unroll
    for (int c = 0; c < 5; c++) {
      ldsm4t(k, c < 4 ? base + 8192 + j * 2048 + lane * 64 + ((c ^ sw) << 4) : base + 24576 + j * 512 + lane * 16);
      mma16816v(s[c], q0, k[0], k[1]); mma16816v(s[c], q1, k[2], k[3]);
    }
  }
  const int tq = 8 * (g >> 1) + 4 * mt + (g & 1);
  const float NEG = -INFINITY;
  float m0 = fmaxf(s[4][0], s[4][1]), m1 = fmaxf(s[4][2], s[4][3]);
#pragma unroll
  for (int c = 0; c < 4; c++) {
    const int tk = 8 * t + 2 * c;
    if (tk > tq) s[c][0] = NEG;
    if (tk + 1 > tq) s[c][1] = NEG;
    if (tk > tq + 2) s[c][2] = NEG;
    if (tk + 1 > tq + 2) s[c][3] = NEG;
    m0 = fmaxf(m0, fmaxf(s[c][0], s[c][1])); m1 = fmaxf(m1, fmaxf(s[c][2], s[c][3]));
  }
  m0 = fmaxf(m0, __shfl_xor_sync(0xffffffffu, m0, 1)); m1 = fmaxf(m1, __shfl_xor_sync(0xffffffffu, m1, 1));
  m0 = fmaxf(m0, __shfl_xor_sync(0xffffffffu, m0, 2)); m1 = fmaxf(m1, __shfl_xor_sync(0xffffffffu, m1, 2));
  const float cs = 0.08838834764831845f * 1.4426950408889634f;
  const float n0 = -m0 * cs, n1 = -m1 * cs;
  float l0 = 0.f, l1 = 0.f;
  uint32_t p[10];
#pragma unroll
  for (int c = 0; c < 5; c++) {
    const float e0 = ex2f(fmaf(s[c][0], cs, n0)), e1 = ex2f(fmaf(s[c][1], cs, n0)), e2 = ex2f(fmaf(s[c][2], cs, n1)), e3 = ex2f(fmaf(s[c][3], cs, n1));
    l0 += e0 + e1; l1 += e2 + e3;
    p[2 * c] = pack_bf16(e0, e1); p[2 * c + 1] = pack_bf16(e2, e3);
  }
  l0 += __shfl_xor_sync(0xffffffffu, l0, 1); l1 += __shfl_xor_sync(0xffffffffu, l1, 1);
  l0 += __shfl_xor_sync(0xffffffffu, l0, 2); l1 += __shfl_xor_sync(0xffffffffu, l1, 2);
  const float i0 = rcpf(l0), i1 = rcpf(l1);
  const uint32_t va = base + 16384 + (lane & 7) * 64 + (((lane >> 3) ^ sw) << 4);
  const uint32_t stg = sb + OFF_STG + warp * 4096;
  const uint32_t sa = stg + (lane & 15) * 256;
#pragma unroll
  for (int j = 0; j < 4; j++) {
    uint32_t vm[4], w[8];
    ldsm4(vm, base + 26624 + j * 512 + lane * 16);
#pragma unroll
    for (int u = 0; u < 4; u++) {
      uint32_t v[4]; float o[4];
      ldsm4(v, va + (j * 4 + u) * 512);
      mma16816z(o, p, v[0], v[1]); mma16816v(o, p + 4, v[2], v[3]); mma1688(o, p[8], p[9], vm[u]);
      w[2 * u] = pack_bf16(o[0] * i0, o[1] * i0); w[2 * u + 1] = pack_bf16(o[2] * i1, o[3] * i1);
    }
    stsm4(sa + (((j * 4 + (lane >> 4)) ^ (lane & 7)) << 4), w[0], w[1], w[2], w[3]);
    stsm4(sa + (((j * 4 + 2 + (lane >> 4)) ^ (lane & 7)) << 4), w[4], w[5], w[6], w[7]);
  }
  __syncwarp();
  if (lane == 0) mbar_arrive_n(sb + B_EMPTY + st * 8, 4);
#pragma unroll
  for (int j = 0; j < 8; j++) {
    const int row = j * 2 + (lane >> 4), ch = lane & 15;
    uint32_t w[4];
    lds128(w, stg + row * 256 + ((ch ^ (row & 7)) << 4));
    const int tok = 8 * ((row & 7) >> 1) + 4 * mt + (row & 1) + 2 * (row >> 3);
    *(uint4*)(g_oB + (size_t)(seg * 32 + tok) * 4096 + head * 128 + ch * 8) = make_uint4(w[0], w[1], w[2], w[3]);
  }
  __syncwarp();
}

__global__ void __launch_bounds__(384, 1) gen_kernel(const __grid_constant__ GMaps tm) {
  using namespace gk;
  extern __shared__ __align__(1024) uint8_t smem_raw[];
  const uint32_t sb = smem_u32(smem_raw);
  const int tid = threadIdx.x, lane = tid & 31;
  const int warp = __shfl_sync(0xffffffffu, tid >> 5, 0);
  if (tid == 0) {
    if ((sb & 0xffffff) != SB0) asm volatile("trap;");
    for (int i = 0; i < 4; i++) { mbar_init(sb + B_FULL + i * 8, 1); mbar_init(sb + B_EMPTY + i * 8, 8); }
    for (int i = 0; i < 2; i++) { mbar_init(sb + B_IFULL + i * 8, 1); mbar_init(sb + B_IEMPTY + i * 8, 10); mbar_init(sb + B_SFULL + i * 8, 4); mbar_init(sb + B_SEMPTY + i * 8, 1); }
    asm volatile("fence.mbarrier_init.release.cluster;" ::: "memory");
  }
  __syncthreads();
  if (warp >= 8) {
    asm volatile("setmaxnreg.dec.sync.aligned.u32 40;");
    if (warp == 8) {
      uint32_t it = 0;
      int held = -1;
      for (uint32_t n_it = 0;; n_it++) {
        int idx = 0;
        if (lane == 0) idx = next_item(held);
        idx = __shfl_sync(0xffffffffu, idx, 0);
        mbar_wait(sb + B_IEMPTY + (n_it & 1) * 8, ((n_it >> 1) & 1) ^ 1);
        if (lane == 0) { sts32(sb + OFF_ITEM + (n_it & 1) * 4, idx); mbar_arrive(sb + B_IFULL + (n_it & 1) * 8); }
        int type, m, n;
        decode_item(idx, type, m, n);
        if (type == T_DONE) break;
        if (type == T_ATA) { for (int b = max((m >> 1) - 2, 0); b <= (m >> 1); b++) wait_count(&g_cnt[C_QKV + b * 8], 24); }
        else if (type == T_OUTA) wait_count(&g_cnt[C_ATA + m * 8], 16);
        else if (type == T_ATB) wait_count(&g_rflag[m], 96);
        else if (type == T_OUTBS) {
          for (int kb = 0; kb < 4; kb++) {
            const uint32_t st = (it + kb) & 3, dst = sb + st * STAGE, bar = sb + B_FULL + st * 8;
            mbar_wait(sb + B_EMPTY + st * 8, (((it + kb) >> 2) & 1) ^ 1);
            if (elect_one()) {
              mbar_arrive_tx(bar, STAGE);
              tma_load_2d(dst + 32768, &tm.Wos, n * 32, kb * 256, bar);
            }
          }
          wait_count(&g_cnt[C_ATB + m * 8], 64);
        }
        else if (type != T_QKV) { wait_count(&g_cnt[C_ATB + 16 * m], 64); wait_count(&g_cnt[C_ATB + 16 * m + 8], 64); }
        asm volatile("fence.proxy.async.global;" ::: "memory");
        if (type == T_ATA) {
          for (int u = 0; u < 8; u++, it++) {
            const uint32_t st = it & 3, dst = sb + st * STAGE, bar = sb + B_FULL + st * 8;
            mbar_wait(sb + B_EMPTY + st * 8, ((it >> 2) & 1) ^ 1);
            if (elect_one()) {
              const int col = (n * 8 + u) * 32, r0 = m * 64 - 256;
              mbar_arrive_tx(bar, 45056);
              tma_load_2d(dst, &tm.qkvQ, col, m * 64, bar);
              tma_load_2d(dst + 4096, &tm.qkvKV, 1024 + col, r0, bar); tma_load_2d(dst + 14336, &tm.qkvKV, 1024 + col, r0 + 160, bar);
              tma_load_2d(dst + 24576, &tm.qkvKV, 2048 + col, r0, bar); tma_load_2d(dst + 34816, &tm.qkvKV, 2048 + col, r0 + 160, bar);
            }
          }
        } else if (type == T_ATB) {
          for (int u = 0; u < (m < SF ? 16 : 4); u++, it++) {
            const uint32_t st = it & 3, dst = sb + st * STAGE, bar = sb + B_FULL + st * 8;
            mbar_wait(sb + B_EMPTY + st * 8, ((it >> 2) & 1) ^ 1);
            if (elect_one()) {
              const int sh = m * 32 + n + u;
              mbar_arrive_tx(bar, 28672);
              bulk_load(dst, (const uint8_t*)g_img + (size_t)sh * 24576, 24576, bar);
              bulk_load(dst + 24576, (const uint8_t*)g_imgm + (size_t)sh * 4096, 4096, bar);
            }
          }
        } else if (type == T_OUTBS) {
          for (int kb = 0; kb < 16; kb++, it++) {
            const uint32_t st = it & 3, dst = sb + st * STAGE, bar = sb + B_FULL + st * 8;
            if (kb >= 4) mbar_wait(sb + B_EMPTY + st * 8, ((it >> 2) & 1) ^ 1);
            if (elect_one()) {
              if (kb >= 4) { mbar_arrive_tx(bar, STAGE); tma_load_2d(dst + 32768, &tm.Wos, n * 32, kb * 256, bar); }
              for (int j = 0; j < 4; j++) tma_load_2d(dst + j * 8192, &tm.oBs, kb * 256 + j * 64, m * 64, bar);
            }
          }
        } else {
          const CUtensorMap* ta = type == T_QKV ? &tm.xA : (type == T_OUTA ? &tm.oA : &tm.oB);
          const CUtensorMap* tb = type == T_QKV ? &tm.wqkv : (type == T_OUTA ? &tm.wo : &tm.Wo);
          const int nkb = type >= T_OUTB ? 64 : 16, nb = type == T_OUTBN ? 1 : (type == T_OUTBM ? 2 : 4);
          for (int kb = 0; kb < nkb; kb++, it++) {
            const uint32_t st = it & 3, dst = sb + st * STAGE, bar = sb + B_FULL + st * 8;
            mbar_wait(sb + B_EMPTY + st * 8, ((it >> 2) & 1) ^ 1);
            if (elect_one()) {
              mbar_arrive_tx(bar, 16384 + nb * 8192);
              tma_load_2d(dst, ta, kb * 64, m * 128, bar);
              for (int j = 0; j < nb; j++) tma_load_2d(dst + 16384 + j * 8192, tb, (n * nb + j) * 64, kb * 64, bar);
            }
          }
        }
      }
    } else if (warp < 11) {
      const int wg = warp - 9;
      const uint32_t stg = sb + OFF_STG + wg * 16384;
      uint32_t ev = 0;
      for (uint32_t n_it = 0;; n_it++) {
        mbar_wait(sb + B_IFULL + (n_it & 1) * 8, (n_it >> 1) & 1);
        const int idx = __shfl_sync(0xffffffffu, (int)lds32(sb + OFF_ITEM + (n_it & 1) * 4), 0);
        if (lane == 0) mbar_arrive(sb + B_IEMPTY + (n_it & 1) * 8);
        int type, m, n;
        decode_item(idx, type, m, n);
        if (type == T_DONE) break;
        if (type == T_ATA || type == T_ATB || type == T_OUTBS) {
          mbar_wait(sb + B_SFULL + wg * 8, ev & 1); ev++;
          if (elect_one()) {
            mbar_arrive(sb + B_SEMPTY + wg * 8);
            if (type != T_OUTBS) signal_count(&g_cnt[(type == T_ATA ? C_ATA : C_ATB) + (m >> 1) * 8], type == T_ATA ? 1 : (m < SF ? 8 : 2));
          }
        } else {
          const CUtensorMap* tc = type == T_QKV ? &tm.qkvSt : &tm.out;
          const int np = type > T_OUTB ? 1 : 2, col = (type >= T_OUTB ? 1024 : 0) + n * (type == T_OUTBN ? 64 : 128 * np), row = m * 128 + wg * 64;
          for (int p = 0; p < np; p++) {
            mbar_wait(sb + B_SFULL + wg * 8, ev & 1); ev++;
            if (elect_one()) {
              tma_store_2d(tc, stg, col + p * 128, row);
              if (type != T_OUTBN) tma_store_2d(tc, stg + 8192, col + p * 128 + 64, row);
              asm volatile("cp.async.bulk.commit_group;" ::: "memory");
              asm volatile("cp.async.bulk.wait_group.read 0;" ::: "memory");
              mbar_arrive(sb + B_SEMPTY + wg * 8);
            }
          }
          if (type == T_QKV && elect_one()) {
            asm volatile("cp.async.bulk.wait_group 0;" ::: "memory");
            asm volatile("fence.proxy.async.global;" ::: "memory");
            signal_count(&g_cnt[C_QKV + m * 8]);
          }
        }
      }
      asm volatile("cp.async.bulk.wait_group 0;" ::: "memory");
      BAR_SYNC(3, 64);
      if (wg == 0) {
        uint32_t last = 0;
        if (lane == 0) { __threadfence(); last = atomicAdd(&g_cnt[C_EXIT], 1) == gridDim.x - 1; }
        if (__shfl_sync(0xffffffffu, last, 0)) {
          for (int i = lane; i < N_CNT; i += 32) g_cnt[i] = 0;
          for (int i = lane; i < 64; i += 32) g_rflag[i] = 0;
        }
      }
    }
  } else {
    asm volatile("setmaxnreg.inc.sync.aligned.u32 232;");
    const int wg = warp >> 2, wq = warp & 3;
    uint32_t it = 0, ev = 0;
    for (uint32_t n_it = 0;; n_it++) {
      mbar_wait(sb + B_IFULL + (n_it & 1) * 8, (n_it >> 1) & 1);
      const int idx = __shfl_sync(0xffffffffu, (int)lds32(sb + OFF_ITEM + (n_it & 1) * 4), 0);
      if (lane == 0) mbar_arrive(sb + B_IEMPTY + (n_it & 1) * 8);
      int type, m, n;
      decode_item(idx, type, m, n);
      if (type == T_DONE) break;
      if (type == T_ATA) {
        mbar_wait(sb + B_SEMPTY + wg * 8, (ev & 1) ^ 1); ev++;
        if (RELAT >= 0 && wg == 1) asm volatile("bar.arrive 1, 256;" ::: "memory");
        for (int u = wg; u < 8; u += 2) {
          const uint32_t i2 = it + u;
          mbar_wait(sb + B_FULL + (i2 & 3) * 8, (i2 >> 2) & 1);
          attn_a_unit(sb, i2 & 3, wg, wq, lane, m, n * 8 + u, u == 7);
        }
        it += 8;
        __syncwarp();
        if (lane == 0) mbar_arrive(sb + B_SFULL + wg * 8);
      } else if (type == T_ATB) {
        mbar_wait(sb + B_SEMPTY + wg * 8, (ev & 1) ^ 1); ev++;
        const int nu = m < SF ? 16 : 4;
        for (int u = warp >> 1; u < nu; u += 4) {
          const uint32_t i2 = it + u;
          mbar_wait(sb + B_FULL + (i2 & 3) * 8, (i2 >> 2) & 1);
          attn_b_unit(sb, i2 & 3, warp, lane, m, n + u);
        }
        it += nu;
        if (lane == 0) mbar_arrive(sb + B_SFULL + wg * 8);
      } else if (type == T_OUTBS) {
        gemm_small(sb, wg, wq, lane, it, ev, tm.outp + (size_t)m * 64 * 2048 + 1024 + n * 32);
      } else if (type == T_OUTBM) {
        gemm_tile<128>(sb, wg, wq, lane, it, ev, 64);
      } else if (type == T_OUTBN) {
        gemm_tile<64>(sb, wg, wq, lane, it, ev, 64);
      } else {
        gemm_tile<256>(sb, wg, wq, lane, it, ev, type == T_OUTB ? 64 : 16);
      }
    }
  }
}
#include <stdio.h>
static RParams g_prm = {48, 256, 448, 704, 448, 672, 500};
static int g_mode = 0, g_ngen = 132;
extern "C" void kernel_launch(void* const* d_in, const int* in_sizes, int n_in, void* d_out, int out_size) {
  static CUtensorMap mq, mk, mv, mo, mx, mp; static GMaps gm; static bool init = false;
  if (!init) {
    init = true;
    const CUtensorMapSwizzle S128 = CU_TENSOR_MAP_SWIZZLE_128B, S64 = CU_TENSOR_MAP_SWIZZLE_64B;
    mq = make_map(d_in[5], 1024, 4096, 4096, 64, 64, S128);
    mk = make_map(d_in[6], 1024, 4096, 4096, 64, 64, S128);
    mv = make_map(d_in[7], 1024, 4096, 4096, 64, 64, S128);
    mo = make_map(d_in[8], 4096, 1024, 1024, 128, 32, S64);
    mx = make_map(d_in[3], 2048, 1024, 1024, 32, 64, S128);
    void *pp, *pq, *pa, *pb;
    cudaGetSymbolAddress(&pp, g_part); cudaGetSymbolAddress(&pq, g_qkvA); cudaGetSymbolAddress(&pa, g_oA); cudaGetSymbolAddress(&pb, g_oB);
    mp = make_map(pp, 72 * 32, 128, 128, 32, 32, CU_TENSOR_MAP_SWIZZLE_NONE, CU_TENSOR_MAP_L2_PROMOTION_NONE);
    gm.xA = make_map(d_in[0], 2048, 1024, 1024, 128, 64, S128);
    gm.wqkv = make_map(d_in[1], 1024, 3072, 3072, 64, 64, S128);
    gm.qkvSt = make_map(pq, 2048, 3072, 3072, 64, 64, S128);
    gm.qkvQ = make_map(pq, 2048, 3072, 3072, 64, 32, S64, CU_TENSOR_MAP_L2_PROMOTION_L2_128B);
    gm.qkvKV = make_map(pq, 2048, 3072, 3072, 160, 32, S64, CU_TENSOR_MAP_L2_PROMOTION_L2_128B);
    gm.oA = make_map(pa, 2048, 1024, 1024, 128, 64, S128);
    gm.wo = make_map(d_in[2], 1024, 1024, 1024, 64, 64, S128);
    gm.oB = make_map(pb, 2048, 4096, 4096, 128, 64, S128);
    gm.Wo = make_map(d_in[8], 4096, 1024, 1024, 64, 64, S128);
    gm.oBs = make_map(pb, 2048, 4096, 4096, 64, 64, S128);
    gm.Wos = make_map(d_in[8], 4096, 1024, 1024, 256, 32, S64, CU_TENSOR_MAP_L2_PROMOTION_L2_128B);
    gm.outp = (__nv_bfloat16*)d_out;
    gm.out = make_map(d_out, 2048, 2048, 2048, 64, 64, S128);
    cudaFuncSetAttribute(rec_kernel, cudaFuncAttributeMaxDynamicSharedMemorySize, rk::SMEM_BYTES);
    cudaFuncSetAttribute(gen_kernel, cudaFuncAttributeMaxDynamicSharedMemorySize, gk::SMEM_BYTES);
  }
  cudaStream_t st = cudaStreamPerThread;
  rec_kernel<<<96, 384, rk::SMEM_BYTES, st>>>(mq, mk, mv, mo, mx, mp, (const __nv_bfloat16*)d_in[4], (const __nv_bfloat16*)d_in[8], g_prm);
  cudaLaunchConfig_t cfg = {};
  cfg.gridDim = dim3(g_ngen); cfg.blockDim = dim3(384); cfg.dynamicSmemBytes = gk::SMEM_BYTES; cfg.stream = st;
  cudaLaunchAttribute at[1];
  at[0].id = cudaLaunchAttributeProgrammaticStreamSerialization; at[0].val.programmaticStreamSerializationAllowed = 1;
  cfg.attrs = at; cfg.numAttrs = g_mode == 0 ? 1 : 0;
  cudaLaunchKernelEx(&cfg, gen_kernel, gm);
}
```
